```python
import torch

def _softmax(x, axis=-1):
    return torch.softmax(x, dim=axis)
def _gelu(x):
    return torch.nn.functional.gelu(x, approximate="tanh")
def _silu(x):
    return torch.nn.functional.silu(x)
def _sigmoid(x):
    return torch.sigmoid(x)
def _layernorm(x, axis=-1, eps=1e-5):
    m = x.mean(dim=axis, keepdim=True)
    v = x.var(dim=axis, keepdim=True, unbiased=False)
    return (x - m) / torch.sqrt(v + eps)
def _scatter_add(tgt, idx, src, axis=0):
    return tgt.clone().index_add_(axis, idx, src)
def _segment_sum(src, seg, n):
    out = torch.zeros((n,) + src.shape[1:], dtype=src.dtype)
    return out.index_add_(0, seg, src)
def _pad(x, pw):
    flat = tuple(v for pair in reversed(pw) for v in pair)
    return torch.nn.functional.pad(x, flat)

kernel_name = 'standalone__kv_cache_quant_int4_int2_kv_with_per_channel_or_per_token_scales__prompt'

def setup_inputs():

    _w = (lambda a: (lambda t: t.to(torch.bfloat16) if t.is_floating_point() else t)(torch.as_tensor(a)))
    B = 1
    Sq = 2048
    Skv = 2048
    Hq = 32
    Hkv = 4
    Dh = 128
    bits = 4
    G = 128
    if G <= 0 or G >= Skv:
        G = max(1, Skv // 2)
    Skv = (Skv // G) * G
    ngk = Skv // G
    qmax = (1 << bits) - 1
    return {
        "q": _w((lambda *s: torch.randn(*s, dtype=torch.bfloat16) * 1.6)(B, Hq, Sq, Dh)),
        "qk": _w(torch.randint(0, qmax + 1, (B, Hkv, Skv, Dh)).to(torch.int32)),
        "qv": _w(torch.randint(0, qmax + 1, (B, Hkv, Skv, Dh)).to(torch.int32)),
        "k_scales": _w(torch.abs((lambda *s: torch.randn(*s, dtype=torch.bfloat16) * 1.6)(B, Hkv, ngk, Dh)) * 0.05 + 0.02),
        "k_zeros": _w((lambda *s: torch.randn(*s, dtype=torch.bfloat16) * 1.6)(B, Hkv, ngk, Dh) + float(qmax) / 2.0),
        "v_scales": _w(torch.abs((lambda *s: torch.randn(*s, dtype=torch.bfloat16) * 0.05)(B, Hkv, Skv, 1)) * 0.05 + 0.02),
        "v_zeros": _w((lambda *s: torch.randn(*s, dtype=torch.bfloat16) * 0.05)(B, Hkv, Skv, 1) + float(qmax) / 2.0),
    }

def reference(q, qk, qv, k_scales, k_zeros, v_scales, v_zeros):
    B, Hq, Sq, Dh = q.shape
    Hkv, Skv = qk.shape[1], qk.shape[2]
    ngk = k_scales.shape[2]
    G = Skv // ngk
    ks = (lambda x, n, axis: torch.repeat_interleave(x, n, dim=axis))(k_scales, G, axis=2)
    kz = (lambda x, n, axis: torch.repeat_interleave(x, n, dim=axis))(k_zeros, G, axis=2)
    k = ((lambda x, dt: x.to(dt))(qk, q.dtype) - kz) * ks
    v = ((lambda x, dt: x.to(dt))(qv, q.dtype) - v_zeros) * v_scales
    rep = Hq // Hkv
    if rep > 1:
        k = (lambda x, n, axis: torch.repeat_interleave(x, n, dim=axis))(k, rep, axis=1)
        v = (lambda x, n, axis: torch.repeat_interleave(x, n, dim=axis))(v, rep, axis=1)
    scale = float(Dh) ** -0.5
    logits = torch.einsum("bhqd,bhkd->bhqk", q, k) * scale
    p = _softmax(logits, axis=-1)
    o = torch.einsum("bhqk,bhkd->bhqd", p, v)
    return o
```

```cpp
#include <cuda_runtime.h>
#include <cuda.h>
#include <cuda_bf16.h>
#include <stdint.h>

namespace {

constexpr int HQ = 32, HKV = 4, SQ = 2048, SKV = 2048, DH = 128;
constexpr int BN = 128;
constexpr int NBLK = SKV / BN;
constexpr int TILE_BYTES = BN * DH * 2;
constexpr int HALF_BYTES = TILE_BYTES / 2;
#define NK_STAGES 3
#ifndef NV_STAGES
#define NV_STAGES 3
#endif
constexpr int NK = NK_STAGES, NV = NV_STAGES;
constexpr int TILES_PER_CTA = 4;
constexpr int NCLUSTERS = 64;
constexpr int SMEM_BYTES = (NK + NV + 1) * TILE_BYTES + 1024 + 256;

__device__ __align__(1024) uint8_t g_kimg[HKV * NBLK * TILE_BYTES];
__device__ __align__(1024) uint8_t g_vimg[HKV * NBLK * TILE_BYTES];

#define TS(e)

__device__ __forceinline__ uint32_t smem_u32(const void* p) { return (uint32_t)__cvta_generic_to_shared(p); }
__device__ __forceinline__ void wg_fence() { asm volatile("wgmma.fence.sync.aligned;\n" ::: "memory"); }
__device__ __forceinline__ void wg_commit() { asm volatile("wgmma.commit_group.sync.aligned;\n" ::: "memory"); }
template <int N> __device__ __forceinline__ void wg_wait() { asm volatile("wgmma.wait_group.sync.aligned %0;\n" ::"n"(N) : "memory"); }
template <int NR> __device__ __forceinline__ void fence_regs(float (&d)[NR]) {
#pragma unroll
  for (int i = 0; i < NR; i++) asm volatile("" : "+f"(d[i])::"memory");
}
template <int NR> __device__ __forceinline__ void fence_regs(uint32_t (&d)[NR]) {
#pragma unroll
  for (int i = 0; i < NR; i++) asm volatile("" : "+r"(d[i])::"memory");
}
__device__ __forceinline__ void bar_sync(int id, int n) { asm volatile("bar.sync %0, %1;\n" ::"r"(id), "r"(n) : "memory"); }
__device__ __forceinline__ void bar_arrive(int id, int n) { asm volatile("bar.arrive %0, %1;\n" ::"r"(id), "r"(n) : "memory"); }
__device__ __forceinline__ void mbar_init(uint32_t bar, uint32_t count) {
  asm volatile("mbarrier.init.shared::cta.b64 [%0], %1;\n" ::"r"(bar), "r"(count) : "memory");
}
__device__ __forceinline__ void mbar_expect_tx(uint32_t bar, uint32_t bytes) {
  asm volatile("mbarrier.arrive.expect_tx.shared::cta.b64 _, [%0], %1;\n" ::"r"(bar), "r"(bytes) : "memory");
}
__device__ __forceinline__ void mbar_wait(uint32_t bar, uint32_t parity) {
  asm volatile(
      "{\n.reg .pred p;\n"
      "WAIT_LOOP:\n"
      "mbarrier.try_wait.parity.shared::cta.b64 p, [%0], %1;\n"
      "@p bra WAIT_DONE;\n"
      "bra WAIT_LOOP;\n"
      "WAIT_DONE:\n}\n" ::"r"(bar), "r"(parity) : "memory");
}
__device__ __forceinline__ uint32_t mbar_test(uint32_t bar, uint32_t parity) {
  uint32_t ok;
  asm volatile("{\n.reg .pred p;\nmbarrier.test_wait.parity.shared::cta.b64 p, [%1], %2;\nselp.u32 %0, 1, 0, p;\n}\n" : "=r"(ok) : "r"(bar), "r"(parity) : "memory");
  return ok;
}
__device__ __forceinline__ void mma_16816(float& c0, float& c1, float& c2, float& c3, uint32_t a0, uint32_t a1, uint32_t a2, uint32_t a3, uint32_t b0, uint32_t b1) {
  asm volatile("mma.sync.aligned.m16n8k16.row.col.f32.bf16.bf16.f32 {%0, %1, %2, %3}, {%4, %5, %6, %7}, {%8, %9}, {%0, %1, %2, %3};\n"
               : "+f"(c0), "+f"(c1), "+f"(c2), "+f"(c3) : "r"(a0), "r"(a1), "r"(a2), "r"(a3), "r"(b0), "r"(b1));
}
__device__ __forceinline__ float rcp_fast(float x) {
  float y;
  asm("rcp.approx.ftz.f32 %0, %1;\n" : "=f"(y) : "f"(x));
  return y;
}
__device__ __forceinline__ void mbar_arrive_local(uint32_t bar) {
  asm volatile("mbarrier.arrive.shared::cta.b64 _, [%0];\n" ::"r"(bar) : "memory");
}
__device__ __forceinline__ void mbar_arrive_cluster(uint32_t bar, uint32_t cta) {
  asm volatile(
      "{\n.reg .b32 ra;\n"
      "mapa.shared::cluster.u32 ra, %0, %1;\n"
      "mbarrier.arrive.shared::cluster.b64 _, [ra];\n}\n" ::"r"(bar), "r"(cta) : "memory");
}
__device__ __forceinline__ void bulk_load_mc(uint32_t dst, const void* src, uint32_t bytes, uint32_t bar, uint16_t mask) {
  asm volatile(
      "cp.async.bulk.shared::cluster.global.mbarrier::complete_tx::bytes.multicast::cluster [%0], [%1], %2, [%3], %4;\n" ::"r"(dst),
      "l"(src), "r"(bytes), "r"(bar), "h"(mask)
      : "memory");
}
__device__ __forceinline__ void bulk_load(uint32_t dst, const void* src, uint32_t bytes, uint32_t bar) {
  asm volatile("cp.async.bulk.shared::cluster.global.mbarrier::complete_tx::bytes [%0], [%1], %2, [%3];\n" ::"r"(dst), "l"(src),
               "r"(bytes), "r"(bar)
               : "memory");
}
__device__ __forceinline__ void tma_load_2d(uint32_t dst, const void* tmap, int c0, int c1, uint32_t bar) {
  asm volatile("cp.async.bulk.tensor.2d.shared::cluster.global.mbarrier::complete_tx::bytes [%0], [%1, {%3, %4}], [%2];\n" ::"r"(dst), "l"(tmap),
               "r"(bar), "r"(c0), "r"(c1)
               : "memory");
}
__device__ __forceinline__ void ldsm_x4(uint32_t& r0, uint32_t& r1, uint32_t& r2, uint32_t& r3, uint32_t addr) {
  asm volatile("ldmatrix.sync.aligned.m8n8.x4.shared.b16 {%0, %1, %2, %3}, [%4];\n" : "=r"(r0), "=r"(r1), "=r"(r2), "=r"(r3) : "r"(addr) : "memory");
}
__device__ __forceinline__ bool wg_any(bool p, int id) {
  uint32_t r;
  asm volatile("{\n.reg .pred p, q;\nsetp.ne.u32 p, %1, 0;\nbarrier.cta.red.or.aligned.pred q, %2, 128, p;\nselp.u32 %0, 1, 0, q;\n}\n"
               : "=r"(r) : "r"((uint32_t)p), "r"(id) : "memory");
  return r != 0;
}
__device__ __forceinline__ float ex2(float x) {
  float y;
  asm("ex2.approx.ftz.f32 %0, %1;\n" : "=f"(y) : "f"(x));
  return y;
}
__device__ __forceinline__ uint32_t pack_bf16(float lo, float hi) {
  uint32_t r;
  asm("cvt.rn.bf16x2.f32 %0, %1, %2;\n" : "=r"(r) : "f"(hi), "f"(lo));
  return r;
}
__device__ __forceinline__ uint64_t make_desc(uint32_t addr, uint32_t lbo, uint32_t sbo) {
  return (uint64_t)((addr & 0x3FFFF) >> 4) | ((uint64_t)(lbo >> 4) << 16) | ((uint64_t)(sbo >> 4) << 32) | (1ull << 62);
}

__device__ __forceinline__ void wgmma_rs_kmaj(float (&d)[64], uint32_t a0, uint32_t a1, uint32_t a2, uint32_t a3, uint64_t descB, int scaleD) {
  asm volatile("{\n.reg .pred p;\nsetp.ne.b32 p, %69, 0;\n"
    "wgmma.mma_async.sync.aligned.m64n128k16.f32.bf16.bf16 "
    "{%0, %1, %2, %3, %4, %5, %6, %7, %8, %9, %10, %11, %12, %13, %14, %15, "
    "%16, %17, %18, %19, %20, %21, %22, %23, %24, %25, %26, %27, %28, %29, %30, %31, "
    "%32, %33, %34, %35, %36, %37, %38, %39, %40, %41, %42, %43, %44, %45, %46, %47, "
    "%48, %49, %50, %51, %52, %53, %54, %55, %56, %57, %58, %59, %60, %61, %62, %63}, "
    "{%64, %65, %66, %67}, %68, p, 1, 1, 0;\n}\n"
    : "+f"(d[0]), "+f"(d[1]), "+f"(d[2]), "+f"(d[3]), "+f"(d[4]), "+f"(d[5]), "+f"(d[6]), "+f"(d[7]),
      "+f"(d[8]), "+f"(d[9]), "+f"(d[10]), "+f"(d[11]), "+f"(d[12]), "+f"(d[13]), "+f"(d[14]), "+f"(d[15]),
      "+f"(d[16]), "+f"(d[17]), "+f"(d[18]), "+f"(d[19]), "+f"(d[20]), "+f"(d[21]), "+f"(d[22]), "+f"(d[23]),
      "+f"(d[24]), "+f"(d[25]), "+f"(d[26]), "+f"(d[27]), "+f"(d[28]), "+f"(d[29]), "+f"(d[30]), "+f"(d[31]),
      "+f"(d[32]), "+f"(d[33]), "+f"(d[34]), "+f"(d[35]), "+f"(d[36]), "+f"(d[37]), "+f"(d[38]), "+f"(d[39]),
      "+f"(d[40]), "+f"(d[41]), "+f"(d[42]), "+f"(d[43]), "+f"(d[44]), "+f"(d[45]), "+f"(d[46]), "+f"(d[47]),
      "+f"(d[48]), "+f"(d[49]), "+f"(d[50]), "+f"(d[51]), "+f"(d[52]), "+f"(d[53]), "+f"(d[54]), "+f"(d[55]),
      "+f"(d[56]), "+f"(d[57]), "+f"(d[58]), "+f"(d[59]), "+f"(d[60]), "+f"(d[61]), "+f"(d[62]), "+f"(d[63])
    : "r"(a0), "r"(a1), "r"(a2), "r"(a3), "l"(descB), "r"(scaleD));
}

__device__ __forceinline__ void wgmma_rs_nmaj(float (&d)[64], uint32_t a0, uint32_t a1, uint32_t a2, uint32_t a3, uint64_t descB, int scaleD) {
  asm volatile("{\n.reg .pred p;\nsetp.ne.b32 p, %69, 0;\n"
    "wgmma.mma_async.sync.aligned.m64n128k16.f32.bf16.bf16 "
    "{%0, %1, %2, %3, %4, %5, %6, %7, %8, %9, %10, %11, %12, %13, %14, %15, "
    "%16, %17, %18, %19, %20, %21, %22, %23, %24, %25, %26, %27, %28, %29, %30, %31, "
    "%32, %33, %34, %35, %36, %37, %38, %39, %40, %41, %42, %43, %44, %45, %46, %47, "
    "%48, %49, %50, %51, %52, %53, %54, %55, %56, %57, %58, %59, %60, %61, %62, %63}, "
    "{%64, %65, %66, %67}, %68, p, 1, 1, 1;\n}\n"
    : "+f"(d[0]), "+f"(d[1]), "+f"(d[2]), "+f"(d[3]), "+f"(d[4]), "+f"(d[5]), "+f"(d[6]), "+f"(d[7]),
      "+f"(d[8]), "+f"(d[9]), "+f"(d[10]), "+f"(d[11]), "+f"(d[12]), "+f"(d[13]), "+f"(d[14]), "+f"(d[15]),
      "+f"(d[16]), "+f"(d[17]), "+f"(d[18]), "+f"(d[19]), "+f"(d[20]), "+f"(d[21]), "+f"(d[22]), "+f"(d[23]),
      "+f"(d[24]), "+f"(d[25]), "+f"(d[26]), "+f"(d[27]), "+f"(d[28]), "+f"(d[29]), "+f"(d[30]), "+f"(d[31]),
      "+f"(d[32]), "+f"(d[33]), "+f"(d[34]), "+f"(d[35]), "+f"(d[36]), "+f"(d[37]), "+f"(d[38]), "+f"(d[39]),
      "+f"(d[40]), "+f"(d[41]), "+f"(d[42]), "+f"(d[43]), "+f"(d[44]), "+f"(d[45]), "+f"(d[46]), "+f"(d[47]),
      "+f"(d[48]), "+f"(d[49]), "+f"(d[50]), "+f"(d[51]), "+f"(d[52]), "+f"(d[53]), "+f"(d[54]), "+f"(d[55]),
      "+f"(d[56]), "+f"(d[57]), "+f"(d[58]), "+f"(d[59]), "+f"(d[60]), "+f"(d[61]), "+f"(d[62]), "+f"(d[63])
    : "r"(a0), "r"(a1), "r"(a2), "r"(a3), "l"(descB), "r"(scaleD));
}

__global__ void __launch_bounds__(256) dequant_kernel(const int* __restrict__ qk, const int* __restrict__ qv,
                                                      const __nv_bfloat16* __restrict__ ks, const __nv_bfloat16* __restrict__ kz,
                                                      const __nv_bfloat16* __restrict__ vs, const __nv_bfloat16* __restrict__ vz) {
  constexpr int ROWS_PER_WARP = 4;
  const int lane = threadIdx.x & 31;
  const int warp = blockIdx.x * 8 + (threadIdx.x >> 5);
  const int row0 = warp * ROWS_PER_WARP;
  const bool isV = row0 >= HKV * SKV;
  const int r0 = isV ? row0 - HKV * SKV : row0;
  const int* src = (isV ? qv : qk) + (size_t)r0 * DH + lane * 4;
  int4 x[ROWS_PER_WARP];
#pragma unroll
  for (int i = 0; i < ROWS_PER_WARP; i++) x[i] = __ldcs(reinterpret_cast<const int4*>(src + i * DH));
  float z[4], s[4];
  if (!isV) {
    const int g = r0 / BN;
    const uint2 zz = *reinterpret_cast<const uint2*>(kz + (size_t)g * DH + lane * 4);
    const uint2 ss = *reinterpret_cast<const uint2*>(ks + (size_t)g * DH + lane * 4);
    z[0] = __uint_as_float(zz.x << 16); z[1] = __uint_as_float(zz.x & 0xffff0000u);
    z[2] = __uint_as_float(zz.y << 16); z[3] = __uint_as_float(zz.y & 0xffff0000u);
    s[0] = __uint_as_float(ss.x << 16); s[1] = __uint_as_float(ss.x & 0xffff0000u);
    s[2] = __uint_as_float(ss.y << 16); s[3] = __uint_as_float(ss.y & 0xffff0000u);
  }
  uint8_t* img = (isV ? g_vimg : g_kimg) + (size_t)(r0 / BN) * TILE_BYTES;
  const int J = lane >> 3, c = (lane & 7) >> 1, sb = lane & 1;
  const int j = 4 * J + 2 * sb + (c & 1);
  const int half = j >> 3, ch = j & 7;
#pragma unroll
  for (int i = 0; i < ROWS_PER_WARP; i++) {
    const int r = r0 + i;
    if (isV) {
      const float zv = __bfloat162float(vz[r]), sv = __bfloat162float(vs[r]);
#pragma unroll
      for (int e = 0; e < 4; e++) { z[e] = zv; s[e] = sv; }
    }
    const int xi[4] = {x[i].x, x[i].y, x[i].z, x[i].w};
    float o[4];
#pragma unroll
    for (int e = 0; e < 4; e++) {
      const float qf = __bfloat162float(__float2bfloat16_rn((float)xi[e]));
      const float df = __bfloat162float(__float2bfloat16_rn(qf - z[e]));
      o[e] = df * s[e];
    }
    const uint32_t p0 = pack_bf16(o[0], o[1]), p1 = pack_bf16(o[2], o[3]);
    const int rr = r & (BN - 1);
    uint2 w;
    if (isV) {
      const uint32_t send = (c & 1) ? p0 : p1;
      const uint32_t recv = __shfl_xor_sync(0xffffffffu, send, 2);
      if (c & 1) { w.x = recv; w.y = p1; } else { w.x = p0; w.y = recv; }
      *reinterpret_cast<uint2*>(img + half * HALF_BYTES + rr * 128 + ((ch ^ (rr & 7)) << 4) + (c >> 1) * 8) = w;
    } else {
      w.x = p0; w.y = p1;
      *reinterpret_cast<uint2*>(img + (lane >> 4) * HALF_BYTES + rr * 128 + ((((lane >> 1) & 7) ^ (rr & 7)) << 4) + (lane & 1) * 8) = w;
    }
  }
}

constexpr float SCALE_LOG2 = 0.08838834764831845f * 1.4426950408889634f;
#define SPLIT 10
constexpr float SUM_THR = 8192.0f;

__device__ __forceinline__ void issue_qk(float (&S)[64], const uint32_t (&Q)[32], uint32_t kaddr) {
  const uint64_t d0 = make_desc(kaddr, 16, 1024);
#pragma unroll
  for (int k = 0; k < 8; k++)
    wgmma_rs_kmaj(S, Q[4 * k], Q[4 * k + 1], Q[4 * k + 2], Q[4 * k + 3], d0 + (uint64_t)(((k & 3) * 32 + (k >> 2) * HALF_BYTES) >> 4), k != 0);
}
__device__ __forceinline__ void issue_pv(float (&O)[64], const uint32_t (&P)[32], uint32_t vaddr, int acc) {
  const uint64_t d0 = make_desc(vaddr, HALF_BYTES, 1024);
#pragma unroll
  for (int k = 0; k < 8; k++)
    wgmma_rs_nmaj(O, P[4 * k], P[4 * k + 1], P[4 * k + 2], P[4 * k + 3], d0 + (uint64_t)((k * 2048) >> 4), (k != 0) | acc);
}

__global__ void __cluster_dims__(2, 1, 1) __launch_bounds__(384, 1)
attn_kernel(const __grid_constant__ CUtensorMap tmq, __nv_bfloat16* __restrict__ out, const uint32_t zero) {
  extern __shared__ uint8_t smem_raw[];
  const uint32_t sbase = (smem_u32(smem_raw) + 1023u) & ~1023u;
  const uint32_t sK = sbase, sV = sbase + NK * TILE_BYTES, sQ = sbase + (NK + NV) * TILE_BYTES;
  const uint32_t bars = sbase + (NK + NV + 1) * TILE_BYTES;
  const uint32_t fullK = bars, fullV = bars + 8 * NK, emptyK = bars + 8 * (NK + NV), emptyV = emptyK + 8 * NK;
  const uint32_t fullQ = emptyV + 8 * NV, emptyQ = fullQ + 8;

  const int warp = __shfl_sync(0xffffffffu, (int)(threadIdx.x >> 5), 0);
  const int lane = threadIdx.x & 31;
  const int wg = warp >> 2;
  const uint32_t rank = blockIdx.x & 1;
  const int cl = blockIdx.x >> 1;
  const int h = cl >> 4;
  const int row0 = h * (8 * SQ) + (cl & 15) * (TILES_PER_CTA * 256) + rank * 128;

  if (threadIdx.x == 0) {
    for (int s = 0; s < NK; s++) { mbar_init(fullK + 8 * s, 1); mbar_init(emptyK + 8 * s, 16); }
    for (int s = 0; s < NV; s++) { mbar_init(fullV + 8 * s, 1); mbar_init(emptyV + 8 * s, 16); }
    mbar_init(fullQ, 1); mbar_init(emptyQ, 8);
    asm volatile("fence.mbarrier_init.release.cluster;\n" ::: "memory");
  }
  asm volatile("barrier.cluster.arrive.release.aligned;\n" ::: "memory");
  asm volatile("barrier.cluster.wait.acquire.aligned;\n" ::: "memory");

  constexpr int TOTAL = TILES_PER_CTA * NBLK;

  if (wg == 0) {
    asm volatile("setmaxnreg.dec.sync.aligned.u32 24;\n");
    if (warp == 3 && lane == 0) {
      const uint8_t* kimg = g_kimg + (size_t)h * NBLK * TILE_BYTES + rank * HALF_BYTES;
      const uint8_t* vimg = g_vimg + (size_t)h * NBLK * TILE_BYTES + rank * HALF_BYTES;
      int ks = 0, kph = 1, vs = 0, vph = 1;
      for (int i = 0; i <= TOTAL; i++) {
        if (i < TOTAL) {
          mbar_wait(emptyK + 8 * ks, kph);
          mbar_expect_tx(fullK + 8 * ks, TILE_BYTES);
          bulk_load_mc(sK + ks * TILE_BYTES + rank * HALF_BYTES, kimg + (size_t)(i & (NBLK - 1)) * TILE_BYTES, HALF_BYTES, fullK + 8 * ks, (uint16_t)3);
          if (++ks == NK) { ks = 0; kph ^= 1; }
        }
        if (i > 0) {
          mbar_wait(emptyV + 8 * vs, vph);
          mbar_expect_tx(fullV + 8 * vs, TILE_BYTES);
          bulk_load_mc(sV + vs * TILE_BYTES + rank * HALF_BYTES, vimg + (size_t)((i - 1) & (NBLK - 1)) * TILE_BYTES, HALF_BYTES, fullV + 8 * vs, (uint16_t)3);
          if (++vs == NV) { vs = 0; vph ^= 1; }
        }
      }
    } else if (warp == 2 && lane == 0) {
      for (int t = 0; t < TILES_PER_CTA; t++) {
        mbar_wait(emptyQ, (t & 1) ^ 1);
        mbar_expect_tx(fullQ, TILE_BYTES);
        tma_load_2d(sQ, &tmq, 0, row0 + t * 256, fullQ);
        tma_load_2d(sQ + HALF_BYTES, &tmq, 64, row0 + t * 256, fullQ);
      }
    }
  } else {
    asm volatile("setmaxnreg.inc.sync.aligned.u32 240;\n");
    const int cw = wg - 1;
    const int wq = warp & 3;
    const int c = lane & 3;
    const int my_bar = 1 + cw, other_bar = 2 - cw, red_bar = 3 + cw;
    __nv_bfloat16* optr = out + ((size_t)row0 + cw * 64 + wq * 16 + (lane >> 2)) * DH + 8 * c;
    const uint32_t qaddr = sQ + (cw * 64 + wq * 16 + (lane & 15)) * 128 + ((((lane >> 4) ^ lane) & 7) << 4);

    float S[64], O[64];
    uint32_t P[32], Q[32];
    float m0, m1, l0, l1;
#pragma unroll
    for (int i = 0; i < 64; i++) { S[i] = 0.f; O[i] = 0.f; }

    auto load_q = [&](int t) {
      mbar_wait(fullQ, t & 1);
#pragma unroll
      for (int k = 0; k < 8; k++) ldsm_x4(Q[4 * k], Q[4 * k + 1], Q[4 * k + 2], Q[4 * k + 3], (qaddr ^ ((k & 3) << 5)) + (k >> 2) * HALF_BYTES);
      fence_regs(Q);
      __syncwarp();
      if (lane == 0) mbar_arrive_local(emptyQ);
    };
    int ks = 0, kph = 0, vs = 0, vph = 0;
    if (cw == 1) bar_arrive(1, 256);
    load_q(0);

    auto release = [&](uint32_t bar) {
      if (lane == 0) { mbar_arrive_cluster(bar, 0); mbar_arrive_cluster(bar, 1); }
    };
    auto rowmax = [&](float& x0, float& x1) {
      x0 = fmaxf(S[0], S[1]); x1 = fmaxf(S[2], S[3]);
      float y0 = fmaxf(S[4], S[5]), y1 = fmaxf(S[6], S[7]);
#pragma unroll
      for (int j = 2; j < 16; j += 2) {
        x0 = fmaxf(x0, fmaxf(S[4 * j], S[4 * j + 1]));
        x1 = fmaxf(x1, fmaxf(S[4 * j + 2], S[4 * j + 3]));
        y0 = fmaxf(y0, fmaxf(S[4 * j + 4], S[4 * j + 5]));
        y1 = fmaxf(y1, fmaxf(S[4 * j + 6], S[4 * j + 7]));
      }
      x0 = fmaxf(x0, y0); x1 = fmaxf(x1, y1);
      x0 = fmaxf(x0, __shfl_xor_sync(0xffffffffu, x0, 1));
      x1 = fmaxf(x1, __shfl_xor_sync(0xffffffffu, x1, 1));
      x0 = fmaxf(x0, __shfl_xor_sync(0xffffffffu, x0, 2));
      x1 = fmaxf(x1, __shfl_xor_sync(0xffffffffu, x1, 2));
    };
    auto exps = [&](int j0, int j1, float b0, float b1, float (&acc)[4]) {
#pragma unroll
      for (int j = 0; j < 16; j++) {
        if (j >= j0 && j < j1) {
          S[4 * j + 0] = ex2(fmaf(S[4 * j + 0], SCALE_LOG2, b0));
          S[4 * j + 1] = ex2(fmaf(S[4 * j + 1], SCALE_LOG2, b0));
          S[4 * j + 2] = ex2(fmaf(S[4 * j + 2], SCALE_LOG2, b1));
          S[4 * j + 3] = ex2(fmaf(S[4 * j + 3], SCALE_LOG2, b1));
          acc[0] += S[4 * j + 0]; acc[1] += S[4 * j + 1]; acc[2] += S[4 * j + 2]; acc[3] += S[4 * j + 3];
        }
      }
    };
    auto convert_p = [&]() {
#pragma unroll
      for (int i = 0; i < 32; i++) P[i] = pack_bf16(S[2 * i], S[2 * i + 1]);
    };
    auto recompute_s = [&](uint32_t kaddr) {
      const uint32_t a0 = kaddr + (lane & 7) * 128 + ((((lane >> 3) ^ lane) & 7) << 4);
#pragma unroll 1
      for (int j = 0; j < 16; j++) {
        float c0 = 0.f, c1 = 0.f, c2 = 0.f, c3 = 0.f;
#pragma unroll
        for (int kq = 0; kq < 4; kq++) {
          uint32_t b0, b1, b2, b3;
          ldsm_x4(b0, b1, b2, b3, ((a0 ^ ((kq & 1) << 6)) + (kq >> 1) * HALF_BYTES + j * 1024));
          mma_16816(c0, c1, c2, c3, Q[8 * kq], Q[8 * kq + 1], Q[8 * kq + 2], Q[8 * kq + 3], b0, b1);
          mma_16816(c0, c1, c2, c3, Q[8 * kq + 4], Q[8 * kq + 5], Q[8 * kq + 6], Q[8 * kq + 7], b2, b3);
        }
#pragma unroll
        for (int t = 0; t < 60; t++) S[t] = S[t + 4];
        S[60] = c0; S[61] = c1; S[62] = c2; S[63] = c3;
      }
    };
    auto epilogue = [&](int tile, float e0, float e1) {
      e0 += __shfl_xor_sync(0xffffffffu, e0, 1); e1 += __shfl_xor_sync(0xffffffffu, e1, 1);
      e0 += __shfl_xor_sync(0xffffffffu, e0, 2); e1 += __shfl_xor_sync(0xffffffffu, e1, 2);
      const float r0 = rcp_fast(e0), r1 = rcp_fast(e1);
      __nv_bfloat16* o = optr + (size_t)tile * 256 * DH;
#pragma unroll
      for (int J = 0; J < 4; J++) {
        uint4 a, b;
        a.x = pack_bf16(O[16 * J + 0] * r0, O[16 * J + 1] * r0);   b.x = pack_bf16(O[16 * J + 2] * r1, O[16 * J + 3] * r1);
        a.y = pack_bf16(O[16 * J + 4] * r0, O[16 * J + 5] * r0);   b.y = pack_bf16(O[16 * J + 6] * r1, O[16 * J + 7] * r1);
        a.z = pack_bf16(O[16 * J + 8] * r0, O[16 * J + 9] * r0);   b.z = pack_bf16(O[16 * J + 10] * r1, O[16 * J + 11] * r1);
        a.w = pack_bf16(O[16 * J + 12] * r0, O[16 * J + 13] * r0); b.w = pack_bf16(O[16 * J + 14] * r1, O[16 * J + 15] * r1);
        *reinterpret_cast<uint4*>(o + 32 * J) = a;
        *reinterpret_cast<uint4*>(o + 8 * DH + 32 * J) = b;
      }
    };

    {
      mbar_wait(fullK + 8 * ks, kph);
      bar_sync(my_bar, 256);
      fence_regs(Q); fence_regs(S);
      wg_fence();
      issue_qk(S, Q, sK + ks * TILE_BYTES);
      wg_commit();
      bar_arrive(other_bar, 256);
      wg_wait<0>();
      fence_regs(S);
      release(emptyK + 8 * ks);
      if (++ks == NK) { ks = 0; kph ^= 1; }
      rowmax(m0, m1);
      float acc[4] = {0.f, 0.f, 0.f, 0.f};
      exps(0, 16, -m0 * SCALE_LOG2, -m1 * SCALE_LOG2, acc);
      convert_p();
      l0 = acc[0] + acc[1]; l1 = acc[2] + acc[3];
      mbar_wait(fullK + 8 * ks, kph);
      mbar_wait(fullV + 8 * vs, vph);
    }
#pragma unroll 1
    for (int i = 0; i < TOTAL - 1; i++) {
      const int blk = i & (NBLK - 1);
      const uint32_t kaddr = sK + ks * TILE_BYTES, vaddr = sV + vs * TILE_BYTES;
      const uint32_t relK = emptyK + 8 * ks, relV = emptyV + 8 * vs;
      if (++ks == NK) { ks = 0; kph ^= 1; }
      if (++vs == NV) { vs = 0; vph ^= 1; }
      const uint32_t nextK = fullK + 8 * ks, nextV = fullV + 8 * vs;
      const bool newtile = (blk == NBLK - 1);
      TS(0);
      bar_sync(my_bar, 256);
      TS(1);
      fence_regs(Q); fence_regs(S); fence_regs(P); fence_regs(O);
      wg_fence();
      issue_qk(S, Q, kaddr);
      wg_commit();
      issue_pv(O, P, vaddr, blk != 0);
      wg_commit();
      bar_arrive(other_bar, 256);
      TS(2);
      const uint32_t okK = (i + 2 < TOTAL) ? mbar_test(nextK, kph) : 1u;
      const uint32_t okV = mbar_test(nextV, vph);
      wg_wait<1>();
      fence_regs(S); fence_regs(Q);
      TS(3);
      const float e0 = l0, e1 = l1;
      if (newtile) { rowmax(m0, m1); l0 = 0.f; l1 = 0.f; }
      float b0 = -m0 * SCALE_LOG2, b1 = -m1 * SCALE_LOG2;
      float acc[4] = {0.f, 0.f, 0.f, 0.f};
      exps(0, SPLIT, b0, b1, acc);
      TS(4);
      if (!okK) mbar_wait(nextK, kph);
      if (!okV) mbar_wait(nextV, vph);
      TS(5);
      wg_wait<0>();
      fence_regs(O); fence_regs(P);
      TS(6);
      release(relV);
      {
        const uint32_t z = __float_as_uint(O[0]) & zero;
        b0 = __uint_as_float(__float_as_uint(b0) | z);
        b1 = __uint_as_float(__float_as_uint(b1) | z);
      }
      exps(SPLIT, 16, b0, b1, acc);
      convert_p();
      float s0 = acc[0] + acc[1], s1 = acc[2] + acc[3];
      if (__any_sync(0xffffffffu, !(fmaxf(s0, s1) <= SUM_THR)) && !newtile) {
        recompute_s(kaddr);
        float x0, x1;
        rowmax(x0, x1);
        x0 = fmaxf(x0, m0); x1 = fmaxf(x1, m1);
        const float a0 = ex2((m0 - x0) * SCALE_LOG2), a1 = ex2((m1 - x1) * SCALE_LOG2);
        m0 = x0; m1 = x1; l0 *= a0; l1 *= a1;
#pragma unroll
        for (int j = 0; j < 16; j++) { O[4 * j] *= a0; O[4 * j + 1] *= a0; O[4 * j + 2] *= a1; O[4 * j + 3] *= a1; }
        acc[0] = acc[1] = acc[2] = acc[3] = 0.f;
        exps(0, 16, -m0 * SCALE_LOG2, -m1 * SCALE_LOG2, acc);
        convert_p();
        s0 = acc[0] + acc[1]; s1 = acc[2] + acc[3];
      }
      l0 += s0; l1 += s1;
      release(relK);
      if (newtile) epilogue(i / NBLK, e0, e1);
      if (blk == NBLK - 2 && i + 2 < TOTAL) load_q((i + 2) / NBLK);
      TS(7);
    }
    {
      bar_sync(my_bar, 256);
      fence_regs(P); fence_regs(O);
      wg_fence();
      issue_pv(O, P, sV + vs * TILE_BYTES, 1);
      wg_commit();
      bar_arrive(other_bar, 256);
      wg_wait<0>();
      fence_regs(O);
      epilogue(TILES_PER_CTA - 1, l0, l1);
    }
    if (cw == 0) bar_sync(1, 256);
  }
  asm volatile("barrier.cluster.arrive.release.aligned;\n" ::: "memory");
  asm volatile("barrier.cluster.wait.acquire.aligned;\n" ::: "memory");
}

}

typedef CUresult (*EncodeTiledFn)(CUtensorMap*, CUtensorMapDataType, cuuint32_t, void*, const cuuint64_t*, const cuuint64_t*, const cuuint32_t*,
                                  const cuuint32_t*, CUtensorMapInterleave, CUtensorMapSwizzle, CUtensorMapL2promotion, CUtensorMapFloatOOBfill);

extern "C" void kernel_launch(void* const* d_in, const int* in_sizes, int n_in, void* d_out, int out_size) {
  const int* qk = (const int*)d_in[1];
  const int* qv = (const int*)d_in[2];
  const __nv_bfloat16* ks = (const __nv_bfloat16*)d_in[3];
  const __nv_bfloat16* kz = (const __nv_bfloat16*)d_in[4];
  const __nv_bfloat16* vs = (const __nv_bfloat16*)d_in[5];
  const __nv_bfloat16* vz = (const __nv_bfloat16*)d_in[6];
  __nv_bfloat16* out = (__nv_bfloat16*)d_out;
  static EncodeTiledFn encode = nullptr;
  if (!encode) {
    cudaFuncSetAttribute(attn_kernel, cudaFuncAttributeMaxDynamicSharedMemorySize, SMEM_BYTES);
    void* fn = nullptr;
    cudaDriverEntryPointQueryResult qres;
    cudaGetDriverEntryPoint("cuTensorMapEncodeTiled", &fn, cudaEnableDefault, &qres);
    encode = (EncodeTiledFn)fn;
  }
  CUtensorMap tmq;
  {
    const cuuint64_t dims[2] = {(cuuint64_t)DH, (cuuint64_t)HQ * SQ};
    const cuuint64_t strides[1] = {(cuuint64_t)DH * 2};
    const cuuint32_t box[2] = {64, 128};
    const cuuint32_t estr[2] = {1, 1};
    encode(&tmq, CU_TENSOR_MAP_DATA_TYPE_BFLOAT16, 2, d_in[0], dims, strides, box, estr, CU_TENSOR_MAP_INTERLEAVE_NONE, CU_TENSOR_MAP_SWIZZLE_128B,
           CU_TENSOR_MAP_L2_PROMOTION_L2_256B, CU_TENSOR_MAP_FLOAT_OOB_FILL_NONE);
  }
  dequant_kernel<<<(2 * HKV * SKV) / (8 * 4), 256>>>(qk, qv, ks, kz, vs, vz);
  attn_kernel<<<2 * NCLUSTERS, 384, SMEM_BYTES>>>(tmq, out, 0u);
}
```

```cpp
#include <cuda_runtime.h>
#include <cuda.h>
#include <cuda_bf16.h>
#include <stdint.h>

namespace {

constexpr int HQ = 32, HKV = 4, SQ = 2048, SKV = 2048, DH = 128;
constexpr int BN = 128;
constexpr int NBLK = SKV / BN;
constexpr int TILE_BYTES = BN * DH * 2;
constexpr int HALF_BYTES = TILE_BYTES / 2;
#define NK_STAGES 3
#ifndef NV_STAGES
#define NV_STAGES 3
#endif
constexpr int NK = NK_STAGES, NV = NV_STAGES;
constexpr int TILES_PER_CTA = 4;
#define CL 2
constexpr int NCTAS = 128;
#define QROWS 32
#define QSLEEP 800
constexpr int QP = 2 * 128 / QROWS;
constexpr int SLICE = (SKV / SKV) * 32768 / CL;
constexpr int SMEM_BYTES = (NK + NV + 1) * TILE_BYTES + 1024 + 256;

__device__ __align__(1024) uint8_t g_kimg[HKV * NBLK * TILE_BYTES];
__device__ __align__(1024) uint8_t g_vimg[HKV * NBLK * TILE_BYTES];

#define TS(e)

__device__ __forceinline__ uint32_t smem_u32(const void* p) { return (uint32_t)__cvta_generic_to_shared(p); }
__device__ __forceinline__ void wg_fence() { asm volatile("wgmma.fence.sync.aligned;\n" ::: "memory"); }
__device__ __forceinline__ void wg_commit() { asm volatile("wgmma.commit_group.sync.aligned;\n" ::: "memory"); }
template <int N> __device__ __forceinline__ void wg_wait() { asm volatile("wgmma.wait_group.sync.aligned %0;\n" ::"n"(N) : "memory"); }
template <int NR> __device__ __forceinline__ void fence_regs(float (&d)[NR]) {
#pragma unroll
  for (int i = 0; i < NR; i++) asm volatile("" : "+f"(d[i])::"memory");
}
template <int NR> __device__ __forceinline__ void fence_regs(uint32_t (&d)[NR]) {
#pragma unroll
  for (int i = 0; i < NR; i++) asm volatile("" : "+r"(d[i])::"memory");
}
__device__ __forceinline__ void bar_sync(int id, int n) { asm volatile("bar.sync %0, %1;\n" ::"r"(id), "r"(n) : "memory"); }
__device__ __forceinline__ void bar_arrive(int id, int n) { asm volatile("bar.arrive %0, %1;\n" ::"r"(id), "r"(n) : "memory"); }
__device__ __forceinline__ void bar_sync_sel(uint32_t second) {
  asm volatile("{\n.reg .pred p;\nsetp.ne.u32 p, %0, 0;\n@!p bar.sync 1, 256;\n@p bar.sync 2, 256;\n}\n" ::"r"(second) : "memory");
}
__device__ __forceinline__ void bar_arrive_sel(uint32_t second) {
  asm volatile("{\n.reg .pred p;\nsetp.ne.u32 p, %0, 0;\n@!p bar.arrive 1, 256;\n@p bar.arrive 2, 256;\n}\n" ::"r"(second) : "memory");
}
__device__ __forceinline__ void mbar_init(uint32_t bar, uint32_t count) {
  asm volatile("mbarrier.init.shared::cta.b64 [%0], %1;\n" ::"r"(bar), "r"(count) : "memory");
}
__device__ __forceinline__ void mbar_expect_tx(uint32_t bar, uint32_t bytes) {
  asm volatile("mbarrier.arrive.expect_tx.shared::cta.b64 _, [%0], %1;\n" ::"r"(bar), "r"(bytes) : "memory");
}
__device__ __forceinline__ void mbar_wait(uint32_t bar, uint32_t parity) {
  asm volatile(
      "{\n.reg .pred p;\n"
      "WAIT_LOOP:\n"
      "mbarrier.try_wait.parity.shared::cta.b64 p, [%0], %1;\n"
      "@p bra WAIT_DONE;\n"
      "bra WAIT_LOOP;\n"
      "WAIT_DONE:\n}\n" ::"r"(bar), "r"(parity) : "memory");
}
__device__ __forceinline__ uint32_t mbar_test(uint32_t bar, uint32_t parity) {
  uint32_t ok;
  asm volatile("{\n.reg .pred p;\nmbarrier.test_wait.parity.shared::cta.b64 p, [%1], %2;\nselp.u32 %0, 1, 0, p;\n}\n" : "=r"(ok) : "r"(bar), "r"(parity) : "memory");
  return ok;
}
__device__ __forceinline__ void mma_16816(float& c0, float& c1, float& c2, float& c3, uint32_t a0, uint32_t a1, uint32_t a2, uint32_t a3, uint32_t b0, uint32_t b1) {
  asm volatile("mma.sync.aligned.m16n8k16.row.col.f32.bf16.bf16.f32 {%0, %1, %2, %3}, {%4, %5, %6, %7}, {%8, %9}, {%0, %1, %2, %3};\n"
               : "+f"(c0), "+f"(c1), "+f"(c2), "+f"(c3) : "r"(a0), "r"(a1), "r"(a2), "r"(a3), "r"(b0), "r"(b1));
}
__device__ __forceinline__ float rcp_fast(float x) {
  float y;
  asm("rcp.approx.ftz.f32 %0, %1;\n" : "=f"(y) : "f"(x));
  return y;
}
__device__ __forceinline__ void mbar_arrive_local(uint32_t bar) {
  asm volatile("mbarrier.arrive.shared::cta.b64 _, [%0];\n" ::"r"(bar) : "memory");
}
__device__ __forceinline__ void mbar_arrive_cluster(uint32_t bar, uint32_t cta) {
  asm volatile(
      "{\n.reg .b32 ra;\n"
      "mapa.shared::cluster.u32 ra, %0, %1;\n"
      "mbarrier.arrive.shared::cluster.b64 _, [ra];\n}\n" ::"r"(bar), "r"(cta) : "memory");
}
__device__ __forceinline__ void bulk_load_mc(uint32_t dst, const void* src, uint32_t bytes, uint32_t bar, uint16_t mask) {
  asm volatile(
      "cp.async.bulk.shared::cluster.global.mbarrier::complete_tx::bytes.multicast::cluster [%0], [%1], %2, [%3], %4;\n" ::"r"(dst),
      "l"(src), "r"(bytes), "r"(bar), "h"(mask)
      : "memory");
}
__device__ __forceinline__ void bulk_load(uint32_t dst, const void* src, uint32_t bytes, uint32_t bar) {
  asm volatile("cp.async.bulk.shared::cluster.global.mbarrier::complete_tx::bytes [%0], [%1], %2, [%3];\n" ::"r"(dst), "l"(src),
               "r"(bytes), "r"(bar)
               : "memory");
}
__device__ __forceinline__ void tma_load_2d(uint32_t dst, const void* tmap, int c0, int c1, uint32_t bar) {
  asm volatile("cp.async.bulk.tensor.2d.shared::cluster.global.mbarrier::complete_tx::bytes [%0], [%1, {%3, %4}], [%2];\n" ::"r"(dst), "l"(tmap),
               "r"(bar), "r"(c0), "r"(c1)
               : "memory");
}
__device__ __forceinline__ void ldsm_x4(uint32_t& r0, uint32_t& r1, uint32_t& r2, uint32_t& r3, uint32_t addr) {
  asm volatile("ldmatrix.sync.aligned.m8n8.x4.shared.b16 {%0, %1, %2, %3}, [%4];\n" : "=r"(r0), "=r"(r1), "=r"(r2), "=r"(r3) : "r"(addr) : "memory");
}
__device__ __forceinline__ bool wg_any(bool p, int id) {
  uint32_t r;
  asm volatile("{\n.reg .pred p, q;\nsetp.ne.u32 p, %1, 0;\nbarrier.cta.red.or.aligned.pred q, %2, 128, p;\nselp.u32 %0, 1, 0, q;\n}\n"
               : "=r"(r) : "r"((uint32_t)p), "r"(id) : "memory");
  return r != 0;
}
__device__ __forceinline__ float ex2(float x) {
  float y;
  asm("ex2.approx.ftz.f32 %0, %1;\n" : "=f"(y) : "f"(x));
  return y;
}
__device__ __forceinline__ uint32_t pack_bf16(float lo, float hi) {
  uint32_t r;
  asm("cvt.rn.bf16x2.f32 %0, %1, %2;\n" : "=r"(r) : "f"(hi), "f"(lo));
  return r;
}
__device__ __forceinline__ uint64_t make_desc(uint32_t addr, uint32_t lbo, uint32_t sbo) {
  return (uint64_t)((addr & 0x3FFFF) >> 4) | ((uint64_t)(lbo >> 4) << 16) | ((uint64_t)(sbo >> 4) << 32) | (1ull << 62);
}

__device__ __forceinline__ void wgmma_rs_kmaj(float (&d)[64], uint32_t a0, uint32_t a1, uint32_t a2, uint32_t a3, uint64_t descB, int scaleD) {
  asm volatile("{\n.reg .pred p;\nsetp.ne.b32 p, %69, 0;\n"
    "wgmma.mma_async.sync.aligned.m64n128k16.f32.bf16.bf16 "
    "{%0, %1, %2, %3, %4, %5, %6, %7, %8, %9, %10, %11, %12, %13, %14, %15, "
    "%16, %17, %18, %19, %20, %21, %22, %23, %24, %25, %26, %27, %28, %29, %30, %31, "
    "%32, %33, %34, %35, %36, %37, %38, %39, %40, %41, %42, %43, %44, %45, %46, %47, "
    "%48, %49, %50, %51, %52, %53, %54, %55, %56, %57, %58, %59, %60, %61, %62, %63}, "
    "{%64, %65, %66, %67}, %68, p, 1, 1, 0;\n}\n"
    : "+f"(d[0]), "+f"(d[1]), "+f"(d[2]), "+f"(d[3]), "+f"(d[4]), "+f"(d[5]), "+f"(d[6]), "+f"(d[7]),
      "+f"(d[8]), "+f"(d[9]), "+f"(d[10]), "+f"(d[11]), "+f"(d[12]), "+f"(d[13]), "+f"(d[14]), "+f"(d[15]),
      "+f"(d[16]), "+f"(d[17]), "+f"(d[18]), "+f"(d[19]), "+f"(d[20]), "+f"(d[21]), "+f"(d[22]), "+f"(d[23]),
      "+f"(d[24]), "+f"(d[25]), "+f"(d[26]), "+f"(d[27]), "+f"(d[28]), "+f"(d[29]), "+f"(d[30]), "+f"(d[31]),
      "+f"(d[32]), "+f"(d[33]), "+f"(d[34]), "+f"(d[35]), "+f"(d[36]), "+f"(d[37]), "+f"(d[38]), "+f"(d[39]),
      "+f"(d[40]), "+f"(d[41]), "+f"(d[42]), "+f"(d[43]), "+f"(d[44]), "+f"(d[45]), "+f"(d[46]), "+f"(d[47]),
      "+f"(d[48]), "+f"(d[49]), "+f"(d[50]), "+f"(d[51]), "+f"(d[52]), "+f"(d[53]), "+f"(d[54]), "+f"(d[55]),
      "+f"(d[56]), "+f"(d[57]), "+f"(d[58]), "+f"(d[59]), "+f"(d[60]), "+f"(d[61]), "+f"(d[62]), "+f"(d[63])
    : "r"(a0), "r"(a1), "r"(a2), "r"(a3), "l"(descB), "r"(scaleD));
}

__device__ __forceinline__ void wgmma_ss_kmaj(float (&d)[64], uint64_t descA, uint64_t descB, int scaleD) {
  asm volatile("{\n.reg .pred p;\nsetp.ne.b32 p, %66, 0;\n"
    "wgmma.mma_async.sync.aligned.m64n128k16.f32.bf16.bf16 "
    "{%0, %1, %2, %3, %4, %5, %6, %7, %8, %9, %10, %11, %12, %13, %14, %15, "
    "%16, %17, %18, %19, %20, %21, %22, %23, %24, %25, %26, %27, %28, %29, %30, %31, "
    "%32, %33, %34, %35, %36, %37, %38, %39, %40, %41, %42, %43, %44, %45, %46, %47, "
    "%48, %49, %50, %51, %52, %53, %54, %55, %56, %57, %58, %59, %60, %61, %62, %63}, "
    "%64, %65, p, 1, 1, 0, 0;\n}\n"
    : "+f"(d[0]), "+f"(d[1]), "+f"(d[2]), "+f"(d[3]), "+f"(d[4]), "+f"(d[5]), "+f"(d[6]), "+f"(d[7]),
      "+f"(d[8]), "+f"(d[9]), "+f"(d[10]), "+f"(d[11]), "+f"(d[12]), "+f"(d[13]), "+f"(d[14]), "+f"(d[15]),
      "+f"(d[16]), "+f"(d[17]), "+f"(d[18]), "+f"(d[19]), "+f"(d[20]), "+f"(d[21]), "+f"(d[22]), "+f"(d[23]),
      "+f"(d[24]), "+f"(d[25]), "+f"(d[26]), "+f"(d[27]), "+f"(d[28]), "+f"(d[29]), "+f"(d[30]), "+f"(d[31]),
      "+f"(d[32]), "+f"(d[33]), "+f"(d[34]), "+f"(d[35]), "+f"(d[36]), "+f"(d[37]), "+f"(d[38]), "+f"(d[39]),
      "+f"(d[40]), "+f"(d[41]), "+f"(d[42]), "+f"(d[43]), "+f"(d[44]), "+f"(d[45]), "+f"(d[46]), "+f"(d[47]),
      "+f"(d[48]), "+f"(d[49]), "+f"(d[50]), "+f"(d[51]), "+f"(d[52]), "+f"(d[53]), "+f"(d[54]), "+f"(d[55]),
      "+f"(d[56]), "+f"(d[57]), "+f"(d[58]), "+f"(d[59]), "+f"(d[60]), "+f"(d[61]), "+f"(d[62]), "+f"(d[63])
    : "l"(descA), "l"(descB), "r"(scaleD));
}

__device__ __forceinline__ void wgmma_rs_nmaj(float (&d)[64], uint32_t a0, uint32_t a1, uint32_t a2, uint32_t a3, uint64_t descB, int scaleD) {
  asm volatile("{\n.reg .pred p;\nsetp.ne.b32 p, %69, 0;\n"
    "wgmma.mma_async.sync.aligned.m64n128k16.f32.bf16.bf16 "
    "{%0, %1, %2, %3, %4, %5, %6, %7, %8, %9, %10, %11, %12, %13, %14, %15, "
    "%16, %17, %18, %19, %20, %21, %22, %23, %24, %25, %26, %27, %28, %29, %30, %31, "
    "%32, %33, %34, %35, %36, %37, %38, %39, %40, %41, %42, %43, %44, %45, %46, %47, "
    "%48, %49, %50, %51, %52, %53, %54, %55, %56, %57, %58, %59, %60, %61, %62, %63}, "
    "{%64, %65, %66, %67}, %68, p, 1, 1, 1;\n}\n"
    : "+f"(d[0]), "+f"(d[1]), "+f"(d[2]), "+f"(d[3]), "+f"(d[4]), "+f"(d[5]), "+f"(d[6]), "+f"(d[7]),
      "+f"(d[8]), "+f"(d[9]), "+f"(d[10]), "+f"(d[11]), "+f"(d[12]), "+f"(d[13]), "+f"(d[14]), "+f"(d[15]),
      "+f"(d[16]), "+f"(d[17]), "+f"(d[18]), "+f"(d[19]), "+f"(d[20]), "+f"(d[21]), "+f"(d[22]), "+f"(d[23]),
      "+f"(d[24]), "+f"(d[25]), "+f"(d[26]), "+f"(d[27]), "+f"(d[28]), "+f"(d[29]), "+f"(d[30]), "+f"(d[31]),
      "+f"(d[32]), "+f"(d[33]), "+f"(d[34]), "+f"(d[35]), "+f"(d[36]), "+f"(d[37]), "+f"(d[38]), "+f"(d[39]),
      "+f"(d[40]), "+f"(d[41]), "+f"(d[42]), "+f"(d[43]), "+f"(d[44]), "+f"(d[45]), "+f"(d[46]), "+f"(d[47]),
      "+f"(d[48]), "+f"(d[49]), "+f"(d[50]), "+f"(d[51]), "+f"(d[52]), "+f"(d[53]), "+f"(d[54]), "+f"(d[55]),
      "+f"(d[56]), "+f"(d[57]), "+f"(d[58]), "+f"(d[59]), "+f"(d[60]), "+f"(d[61]), "+f"(d[62]), "+f"(d[63])
    : "r"(a0), "r"(a1), "r"(a2), "r"(a3), "l"(descB), "r"(scaleD));
}

__global__ void __launch_bounds__(256) dequant_kernel(const int* __restrict__ qk, const int* __restrict__ qv,
                                                      const __nv_bfloat16* __restrict__ ks, const __nv_bfloat16* __restrict__ kz,
                                                      const __nv_bfloat16* __restrict__ vs, const __nv_bfloat16* __restrict__ vz) {
  constexpr int ROWS_PER_WARP = 4;
  const int lane = threadIdx.x & 31;
  const int warp = blockIdx.x * 8 + (threadIdx.x >> 5);
  const int row0 = warp * ROWS_PER_WARP;
  const bool isV = row0 >= HKV * SKV;
  const int r0 = isV ? row0 - HKV * SKV : row0;
  const int* src = (isV ? qv : qk) + (size_t)r0 * DH + lane * 4;
  int4 x[ROWS_PER_WARP];
#pragma unroll
  for (int i = 0; i < ROWS_PER_WARP; i++) x[i] = __ldcs(reinterpret_cast<const int4*>(src + i * DH));
  float z[4], s[4];
  if (!isV) {
    const int g = r0 / BN;
    const uint2 zz = *reinterpret_cast<const uint2*>(kz + (size_t)g * DH + lane * 4);
    const uint2 ss = *reinterpret_cast<const uint2*>(ks + (size_t)g * DH + lane * 4);
    z[0] = __uint_as_float(zz.x << 16); z[1] = __uint_as_float(zz.x & 0xffff0000u);
    z[2] = __uint_as_float(zz.y << 16); z[3] = __uint_as_float(zz.y & 0xffff0000u);
    s[0] = __uint_as_float(ss.x << 16); s[1] = __uint_as_float(ss.x & 0xffff0000u);
    s[2] = __uint_as_float(ss.y << 16); s[3] = __uint_as_float(ss.y & 0xffff0000u);
  }
  uint8_t* img = (isV ? g_vimg : g_kimg) + (size_t)(r0 / BN) * TILE_BYTES;
  const int J = lane >> 3, c = (lane & 7) >> 1, sb = lane & 1;
  const int j = 4 * J + 2 * sb + (c & 1);
  const int half = j >> 3, ch = j & 7;
#pragma unroll
  for (int i = 0; i < ROWS_PER_WARP; i++) {
    const int r = r0 + i;
    if (isV) {
      const float zv = __bfloat162float(vz[r]), sv = __bfloat162float(vs[r]);
#pragma unroll
      for (int e = 0; e < 4; e++) { z[e] = zv; s[e] = sv; }
    }
    const int xi[4] = {x[i].x, x[i].y, x[i].z, x[i].w};
    float o[4];
#pragma unroll
    for (int e = 0; e < 4; e++) {
      const float qf = __bfloat162float(__float2bfloat16_rn((float)xi[e]));
      const float df = __bfloat162float(__float2bfloat16_rn(qf - z[e]));
      o[e] = df * s[e];
    }
    const uint32_t p0 = pack_bf16(o[0], o[1]), p1 = pack_bf16(o[2], o[3]);
    const int rr = r & (BN - 1);
    uint2 w;
    if (isV) {
      const uint32_t send = (c & 1) ? p0 : p1;
      const uint32_t recv = __shfl_xor_sync(0xffffffffu, send, 2);
      if (c & 1) { w.x = recv; w.y = p1; } else { w.x = p0; w.y = recv; }
      *reinterpret_cast<uint2*>(img + half * HALF_BYTES + rr * 128 + ((ch ^ (rr & 7)) << 4) + (c >> 1) * 8) = w;
    } else {
      w.x = p0; w.y = p1;
      *reinterpret_cast<uint2*>(img + (lane >> 4) * HALF_BYTES + rr * 128 + ((((lane >> 1) & 7) ^ (rr & 7)) << 4) + (lane & 1) * 8) = w;
    }
  }
}

constexpr float SCALE_LOG2 = 0.08838834764831845f * 1.4426950408889634f;
#define SPLIT 5
#define DEPD 2
constexpr float SUM_THR = 4294967296.0f;

__device__ __forceinline__ void issue_qk(float (&S)[64], const uint32_t (&Q)[32], uint32_t kaddr) {
  const uint64_t d0 = make_desc(kaddr, 16, 1024);
#pragma unroll
  for (int k = 0; k < 8; k++)
    wgmma_rs_kmaj(S, Q[4 * k], Q[4 * k + 1], Q[4 * k + 2], Q[4 * k + 3], d0 + (uint64_t)(((k & 3) * 32 + (k >> 2) * HALF_BYTES) >> 4), k != 0);
}
__device__ __forceinline__ void issue_qk_ss(float (&S)[64], uint32_t qaddr, uint32_t kaddr) {
  const uint64_t a0 = make_desc(qaddr, 16, 1024), d0 = make_desc(kaddr, 16, 1024);
#pragma unroll
  for (int k = 0; k < 8; k++) {
    const uint64_t off = (uint64_t)(((k & 3) * 32 + (k >> 2) * HALF_BYTES) >> 4);
    wgmma_ss_kmaj(S, a0 + off, d0 + off, k != 0);
  }
}
__device__ __forceinline__ void issue_pv(float (&O)[64], const uint32_t (&P)[32], uint32_t vaddr, int acc) {
  const uint64_t d0 = make_desc(vaddr, HALF_BYTES, 1024);
#pragma unroll
  for (int k = 0; k < 8; k++)
    wgmma_rs_nmaj(O, P[4 * k], P[4 * k + 1], P[4 * k + 2], P[4 * k + 3], d0 + (uint64_t)((k * 2048) >> 4), (k != 0) | acc);
}
__device__ __forceinline__ float tie(float a, float b, uint32_t z) {
  uint32_t r;
  asm("lop3.b32 %0, %1, %2, %3, 0xF8;\n" : "=r"(r) : "r"(__float_as_uint(a)), "r"(__float_as_uint(b)), "r"(z));
  return __uint_as_float(r);
}

__device__ __forceinline__ uint32_t tieu(uint32_t a, float b, uint32_t z) {
  uint32_t r;
  asm("lop3.b32 %0, %1, %2, %3, 0xF8;\n" : "=r"(r) : "r"(a), "r"(__float_as_uint(b)), "r"(z));
  return r;
}

#define BAR_SYNC_MINE bar_sync(my_bar, 256)
#define BAR_ARRIVE_OTHER bar_arrive(other_bar, 256)
#define LDSM_POS 0
template <bool B> struct BoolC { static constexpr bool value = B; };

__global__ void __cluster_dims__(CL, 1, 1) __launch_bounds__(384, 1)
attn_kernel(const __grid_constant__ CUtensorMap tmq, const __nv_bfloat16* __restrict__ q, __nv_bfloat16* __restrict__ out, const uint32_t zero) {
  extern __shared__ uint8_t smem_raw[];
  const uint32_t sbase = (smem_u32(smem_raw) + 1023u) & ~1023u;
  const uint32_t sK = sbase, sV = sbase + NK * TILE_BYTES, sQ = sbase + (NK + NV) * TILE_BYTES;
  const uint32_t bars = sbase + (NK + NV + 1) * TILE_BYTES;
  const uint32_t fullK = bars, fullV = bars + 8 * NK, emptyK = bars + 8 * (NK + NV), emptyV = emptyK + 8 * NK;
  const uint32_t fullQ = emptyV + 8 * NV, emptyQ = fullQ + 8;

  const int warp = __shfl_sync(0xffffffffu, (int)(threadIdx.x >> 5), 0);
  const int lane = threadIdx.x & 31;
  const int wg = warp >> 2;
  const uint32_t rank = blockIdx.x & (CL - 1);
  const int h = blockIdx.x >> 5;
  const int row0 = blockIdx.x * (TILES_PER_CTA * 128);

  if (threadIdx.x == 0) {
    for (int s = 0; s < NK; s++) { mbar_init(fullK + 8 * s, 1); mbar_init(emptyK + 8 * s, 8 * CL); }
    for (int s = 0; s < NV; s++) { mbar_init(fullV + 8 * s, 1); mbar_init(emptyV + 8 * s, 8 * CL); }
    mbar_init(fullQ, 1); mbar_init(emptyQ, 8);
    asm volatile("fence.mbarrier_init.release.cluster;\n" ::: "memory");
    mbar_expect_tx(fullQ, TILE_BYTES);
    for (int p = 0; p < QP; p++) tma_load_2d(sQ + (p & 1) * HALF_BYTES + (p >> 1) * (QROWS * 128), &tmq, (p & 1) * 64, row0 + (p >> 1) * QROWS, fullQ);
  }
  asm volatile("barrier.cluster.arrive.relaxed.aligned;\n" ::: "memory");
  asm volatile("barrier.cluster.wait.aligned;\n" ::: "memory");

  constexpr int TOTAL = TILES_PER_CTA * NBLK;

  if (wg == 0) {
    asm volatile("setmaxnreg.dec.sync.aligned.u32 24;\n");
    if (warp == 3 && lane == 0) {
      const uint8_t* kimg = g_kimg + (size_t)h * NBLK * TILE_BYTES + rank * SLICE;
      const uint8_t* vimg = g_vimg + (size_t)h * NBLK * TILE_BYTES + rank * SLICE;
      int ks = 0, kph = 1, vs = 0, vph = 1;
      for (int i = 0; i <= TOTAL; i++) {
        if (i < TOTAL) {
          mbar_wait(emptyK + 8 * ks, kph);
          mbar_expect_tx(fullK + 8 * ks, TILE_BYTES);
          bulk_load_mc(sK + ks * TILE_BYTES + rank * SLICE, kimg + (size_t)(i & (NBLK - 1)) * TILE_BYTES, SLICE, fullK + 8 * ks, (uint16_t)((1 << CL) - 1));
          if (++ks == NK) { ks = 0; kph ^= 1; }
        }
        if (i > 0) {
          mbar_wait(emptyV + 8 * vs, vph);
          mbar_expect_tx(fullV + 8 * vs, TILE_BYTES);
          bulk_load_mc(sV + vs * TILE_BYTES + rank * SLICE, vimg + (size_t)((i - 1) & (NBLK - 1)) * TILE_BYTES, SLICE, fullV + 8 * vs, (uint16_t)((1 << CL) - 1));
          if (++vs == NV) { vs = 0; vph ^= 1; }
        }
      }
    } else if (warp == 2 && lane == 0) {
      for (int t = 1; t < TILES_PER_CTA; t++) {
        mbar_wait(emptyQ, (t & 1) ^ 1);
        mbar_expect_tx(fullQ, TILE_BYTES);
        for (int p = 0; p < QP; p++) {
          tma_load_2d(sQ + (p & 1) * HALF_BYTES + (p >> 1) * (QROWS * 128), &tmq, (p & 1) * 64, row0 + t * 128 + (p >> 1) * QROWS, fullQ);
          __nanosleep(QSLEEP);
        }
      }
    }
  } else {
    asm volatile("setmaxnreg.inc.sync.aligned.u32 240;\n");
    uint32_t tid;
    asm volatile("mov.u32 %0, %%tid.x;\n" : "=r"(tid));
    const int my_bar = tid >> 7, other_bar = 3 - my_bar;
    const int cw = my_bar - 1;
    const int wq = (tid >> 5) & 3;
    const int c = lane & 3;
    const int myrow = row0 + cw * 64 + wq * 16 + (lane >> 2);
    __nv_bfloat16* optr = out + (size_t)myrow * DH + 8 * c;
    const uint32_t qaddr = sQ + (cw * 64 + wq * 16 + (lane & 15)) * 128 + ((((lane >> 4) ^ lane) & 7) << 4);

    float S[64], O[64];
    uint32_t P[32], Q[32];
    float m0, m1, l0 = 0.f, l1 = 0.f;
    float s0, s1;
#pragma unroll
    for (int i = 0; i < 64; i++) { S[i] = 0.f; O[i] = 0.f; }

    auto ldsm_q = [&]() {
#pragma unroll
      for (int k = 0; k < 8; k++) ldsm_x4(Q[4 * k], Q[4 * k + 1], Q[4 * k + 2], Q[4 * k + 3], (qaddr ^ ((k & 3) << 5)) + (k >> 2) * HALF_BYTES);
    };
    auto release = [&](uint32_t bar) {
      if (lane < CL) mbar_arrive_cluster(bar, lane);
    };
    auto exps = [&](int k0, int k1, float b0, float b1, float (&hist)[8][2]) {
#pragma unroll
      for (int k = 0; k < 8; k++) {
        if (k >= k0 && k < k1) {
          float c0 = b0, c1 = b1;
          if (k - DEPD >= 0) { c0 = tie(b0, hist[k - DEPD][0], zero); c1 = tie(b1, hist[k - DEPD][1], zero); }
          float a0 = k ? hist[k - 1][0] : 0.f, a1 = k ? hist[k - 1][1] : 0.f;
#pragma unroll
          for (int j = 2 * k; j < 2 * k + 2; j++) {
            S[4 * j + 0] = ex2(fmaf(S[4 * j + 0], SCALE_LOG2, c0));
            S[4 * j + 1] = ex2(fmaf(S[4 * j + 1], SCALE_LOG2, c0));
            S[4 * j + 2] = ex2(fmaf(S[4 * j + 2], SCALE_LOG2, c1));
            S[4 * j + 3] = ex2(fmaf(S[4 * j + 3], SCALE_LOG2, c1));
            if (j == 0) { a0 = S[0] + S[1]; a1 = S[2] + S[3]; }
            else { a0 += S[4 * j + 0]; a0 += S[4 * j + 1]; a1 += S[4 * j + 2]; a1 += S[4 * j + 3]; }
          }
          hist[k][0] = a0; hist[k][1] = a1;
        }
      }
    };
    auto convert_p = [&]() {
#pragma unroll
      for (int i = 0; i < 32; i++) P[i] = pack_bf16(S[2 * i], S[2 * i + 1]);
    };
    auto redo_block = [&](uint32_t kaddr, int tile) {
      const uint32_t* qp = reinterpret_cast<const uint32_t*>(q + ((size_t)myrow + tile * 128) * DH) + c;
#pragma unroll
      for (int k = 0; k < 8; k++) {
        P[4 * k] = qp[8 * k]; P[4 * k + 1] = qp[8 * k + 4 * DH]; P[4 * k + 2] = qp[8 * k + 4]; P[4 * k + 3] = qp[8 * k + 4 + 4 * DH];
      }
      const uint32_t a0 = kaddr + (lane & 7) * 128 + ((((lane >> 3) ^ lane) & 7) << 4);
      float T[64];
      float x0 = m0, x1 = m1;
#pragma unroll 1
      for (int j = 0; j < 16; j++) {
        float c0 = 0.f, c1 = 0.f, c2 = 0.f, c3 = 0.f;
#pragma unroll
        for (int kq = 0; kq < 4; kq++) {
          uint32_t b0, b1, b2, b3;
          ldsm_x4(b0, b1, b2, b3, ((a0 ^ ((kq & 1) << 6)) + (kq >> 1) * HALF_BYTES + j * 1024));
          mma_16816(c0, c1, c2, c3, P[8 * kq], P[8 * kq + 1], P[8 * kq + 2], P[8 * kq + 3], b0, b1);
          mma_16816(c0, c1, c2, c3, P[8 * kq + 4], P[8 * kq + 5], P[8 * kq + 6], P[8 * kq + 7], b2, b3);
        }
        T[4 * j] = c0; T[4 * j + 1] = c1; T[4 * j + 2] = c2; T[4 * j + 3] = c3;
        x0 = fmaxf(x0, fmaxf(c0, c1)); x1 = fmaxf(x1, fmaxf(c2, c3));
      }
      x0 = fmaxf(x0, __shfl_xor_sync(0xffffffffu, x0, 1)); x1 = fmaxf(x1, __shfl_xor_sync(0xffffffffu, x1, 1));
      x0 = fmaxf(x0, __shfl_xor_sync(0xffffffffu, x0, 2)); x1 = fmaxf(x1, __shfl_xor_sync(0xffffffffu, x1, 2));
      const float a0f = ex2((m0 - x0) * SCALE_LOG2), a1f = ex2((m1 - x1) * SCALE_LOG2);
      m0 = x0; m1 = x1; l0 *= a0f; l1 *= a1f;
#pragma unroll
      for (int j = 0; j < 16; j++) { O[4 * j] *= a0f; O[4 * j + 1] *= a0f; O[4 * j + 2] *= a1f; O[4 * j + 3] *= a1f; }
      const float b0 = -m0 * SCALE_LOG2, b1 = -m1 * SCALE_LOG2;
      s0 = 0.f; s1 = 0.f;
      uint32_t U[32];
#pragma unroll 1
      for (int j = 0; j < 16; j++) {
        const float e0 = ex2(fmaf(T[4 * j], SCALE_LOG2, b0)), e1 = ex2(fmaf(T[4 * j + 1], SCALE_LOG2, b0));
        const float e2 = ex2(fmaf(T[4 * j + 2], SCALE_LOG2, b1)), e3 = ex2(fmaf(T[4 * j + 3], SCALE_LOG2, b1));
        s0 += e0 + e1; s1 += e2 + e3;
        U[2 * j] = pack_bf16(e0, e1); U[2 * j + 1] = pack_bf16(e2, e3);
      }
#pragma unroll
      for (int i = 0; i < 32; i++) P[i] = U[i];
    };
    auto pack_o = [&](float r0, float r1) {
#pragma unroll
      for (int J = 0; J < 4; J++) {
        float* o = &O[16 * J];
        asm volatile("{\n.reg .f32 t<16>;\n.reg .b32 u<8>;\n"
            "mul.f32 t0, %0, %16;\nmul.f32 t1, %1, %16;\nmul.f32 t2, %2, %17;\nmul.f32 t3, %3, %17;\n"
            "mul.f32 t4, %4, %16;\nmul.f32 t5, %5, %16;\nmul.f32 t6, %6, %17;\nmul.f32 t7, %7, %17;\n"
            "mul.f32 t8, %8, %16;\nmul.f32 t9, %9, %16;\nmul.f32 t10, %10, %17;\nmul.f32 t11, %11, %17;\n"
            "mul.f32 t12, %12, %16;\nmul.f32 t13, %13, %16;\nmul.f32 t14, %14, %17;\nmul.f32 t15, %15, %17;\n"
            "cvt.rn.bf16x2.f32 u0, t1, t0;\ncvt.rn.bf16x2.f32 u1, t5, t4;\ncvt.rn.bf16x2.f32 u2, t9, t8;\ncvt.rn.bf16x2.f32 u3, t13, t12;\n"
            "cvt.rn.bf16x2.f32 u4, t3, t2;\ncvt.rn.bf16x2.f32 u5, t7, t6;\ncvt.rn.bf16x2.f32 u6, t11, t10;\ncvt.rn.bf16x2.f32 u7, t15, t14;\n"
            "mov.b32 %0, u0;\nmov.b32 %1, u1;\nmov.b32 %2, u2;\nmov.b32 %3, u3;\n"
            "mov.b32 %4, u4;\nmov.b32 %5, u5;\nmov.b32 %6, u6;\nmov.b32 %7, u7;\n}\n"
            : "+f"(o[0]), "+f"(o[1]), "+f"(o[2]), "+f"(o[3]), "+f"(o[4]), "+f"(o[5]), "+f"(o[6]), "+f"(o[7]),
              "+f"(o[8]), "+f"(o[9]), "+f"(o[10]), "+f"(o[11]), "+f"(o[12]), "+f"(o[13]), "+f"(o[14]), "+f"(o[15])
            : "f"(r0), "f"(r1));
      }
    };
    auto store_o = [&](int tile) {
      __nv_bfloat16* o = optr + (size_t)tile * 128 * DH;
#pragma unroll
      for (int J = 0; J < 4; J++) {
        asm volatile("st.global.v4.b32 [%0], {%1, %2, %3, %4};\n" :: "l"(o + 32 * J), "f"(O[16 * J]), "f"(O[16 * J + 1]), "f"(O[16 * J + 2]), "f"(O[16 * J + 3]) : "memory");
        asm volatile("st.global.v4.b32 [%0], {%1, %2, %3, %4};\n" :: "l"(o + 8 * DH + 32 * J), "f"(O[16 * J + 4]), "f"(O[16 * J + 5]), "f"(O[16 * J + 6]), "f"(O[16 * J + 7]) : "memory");
      }
    };
#define EPI_MODE 1
#define STORE_AT_SETTLE store_o((i >> 4) - 1)
    auto settle = [&](int i, uint32_t kprev) {
      const int blk = i & (NBLK - 1);
      if (blk == 0) {
        if (i > 0) STORE_AT_SETTLE;
        l0 = 0.f; l1 = 0.f;
      }
      if (__any_sync(0xffffffffu, !(s0 <= SUM_THR) || !(s1 <= SUM_THR))) redo_block(kprev, i >> 4);
      l0 += s0; l1 += s1;
      if (blk == NBLK - 1) {
        l0 += __shfl_xor_sync(0xffffffffu, l0, 1); l1 += __shfl_xor_sync(0xffffffffu, l1, 1);
        l0 += __shfl_xor_sync(0xffffffffu, l0, 2); l1 += __shfl_xor_sync(0xffffffffu, l1, 2);
        l0 = rcp_fast(l0); l1 = rcp_fast(l1);
      }
    };

    int ks = 0, kph = 0, vs = 0, vph = 0;
    uint32_t kprev = sK, relKprev = emptyK;
    if (cw == 1) bar_arrive(1, 256);
    mbar_wait(fullQ, 0);
    ldsm_q();

    {
      mbar_wait(fullK, 0);
      BAR_SYNC_MINE;
      fence_regs(Q); fence_regs(S);
      wg_fence();
      issue_qk(S, Q, sK);
      wg_commit();
      BAR_ARRIVE_OTHER;
      if (lane == 0) mbar_arrive_local(emptyQ);
      ks = 1;
      wg_wait<0>();
      fence_regs(S);
      m0 = __shfl_sync(0xffffffffu, S[0], lane & ~3); m1 = __shfl_sync(0xffffffffu, S[2], lane & ~3);
      float hist[8][2];
      exps(0, 8, -m0 * SCALE_LOG2, -m1 * SCALE_LOG2, hist);
      convert_p();
      s0 = hist[7][0]; s1 = hist[7][1];
      mbar_wait(fullK + 8 * ks, kph);
      mbar_wait(fullV + 8 * vs, vph);
    }
    auto iteration = [&](auto pre_c, int i) {
      constexpr bool PRE = decltype(pre_c)::value;
      const int blk = PRE ? NBLK - 2 : (i & (NBLK - 1));
      const uint32_t kaddr = sK + ks * TILE_BYTES, vaddr = sV + vs * TILE_BYTES;
      const uint32_t relK = emptyK + 8 * ks, relV = emptyV + 8 * vs;
      if (++ks == NK) { ks = 0; kph ^= 1; }
      if (++vs == NV) { vs = 0; vph ^= 1; }
      const uint32_t nextK = fullK + 8 * ks, nextV = fullV + 8 * vs;
      BAR_SYNC_MINE;
      fence_regs(Q); fence_regs(S);
      wg_fence();
      issue_qk(S, Q, kaddr);
      wg_commit();
      settle(i, kprev);
      release(relKprev);
      kprev = kaddr; relKprev = relK;
      fence_regs(P); fence_regs(O);
      wg_fence();
      issue_pv(O, P, vaddr, blk != 0);
      wg_commit();
      BAR_ARRIVE_OTHER;
      if (PRE) mbar_wait(fullQ, ((i + 2) >> 4) & 1);
      else if (blk == NBLK - 1 && lane == 0) mbar_arrive_local(emptyQ);
      wg_wait<1>();
      fence_regs(S); fence_regs(Q);
      if (PRE) { if (LDSM_POS == 0) ldsm_q(); }
      else if (blk == NBLK - 1) { m0 = __shfl_sync(0xffffffffu, S[0], lane & ~3); m1 = __shfl_sync(0xffffffffu, S[2], lane & ~3); }
      const float b0 = -m0 * SCALE_LOG2, b1 = -m1 * SCALE_LOG2;
      float hist[8][2];
      exps(0, 8, b0, b1, hist);
      const uint32_t tK = mbar_test(nextK, tieu(kph, hist[SPLIT - 1][0], zero));
      const uint32_t tV = mbar_test(nextV, tieu(vph, hist[SPLIT - 1][1], zero));
      wg_wait<0>();
      const bool okK = __all_sync(0xffffffffu, tK) || (i + 2 >= TOTAL);
      const bool okV = __all_sync(0xffffffffu, tV);
      fence_regs(O); fence_regs(P);
      release(relV);
      convert_p();
      s0 = hist[7][0]; s1 = hist[7][1];
      if (PRE && LDSM_POS == 1) ldsm_q();
      if (!PRE && blk == NBLK - 1) {
        pack_o(l0, l1);
      }
      if (!okK) mbar_wait(nextK, kph);
      if (!okV) mbar_wait(nextV, vph);
    };
#pragma unroll 1
    for (int i = 0; i < TOTAL - 1; i++) {
      if ((i & (NBLK - 1)) == NBLK - 2 && i + 2 < TOTAL) iteration(BoolC<true>(), i);
      else iteration(BoolC<false>(), i);
    }
    {
      settle(TOTAL - 1, kprev);
      BAR_SYNC_MINE;
      fence_regs(P); fence_regs(O);
      wg_fence();
      issue_pv(O, P, sV + vs * TILE_BYTES, 1);
      wg_commit();
      BAR_ARRIVE_OTHER;
      wg_wait<0>();
      fence_regs(O);
      pack_o(l0, l1);
      store_o(TILES_PER_CTA - 1);
    }
    if (cw == 0) bar_sync(1, 256);
  }
  asm volatile("barrier.cluster.arrive.relaxed.aligned;\n" ::: "memory");
  asm volatile("barrier.cluster.wait.aligned;\n" ::: "memory");
}

}

typedef CUresult (*EncodeTiledFn)(CUtensorMap*, CUtensorMapDataType, cuuint32_t, void*, const cuuint64_t*, const cuuint64_t*, const cuuint32_t*,
                                  const cuuint32_t*, CUtensorMapInterleave, CUtensorMapSwizzle, CUtensorMapL2promotion, CUtensorMapFloatOOBfill);

extern "C" void kernel_launch(void* const* d_in, const int* in_sizes, int n_in, void* d_out, int out_size) {
  const int* qk = (const int*)d_in[1];
  const int* qv = (const int*)d_in[2];
  const __nv_bfloat16* ks = (const __nv_bfloat16*)d_in[3];
  const __nv_bfloat16* kz = (const __nv_bfloat16*)d_in[4];
  const __nv_bfloat16* vs = (const __nv_bfloat16*)d_in[5];
  const __nv_bfloat16* vz = (const __nv_bfloat16*)d_in[6];
  __nv_bfloat16* out = (__nv_bfloat16*)d_out;
  static EncodeTiledFn encode = nullptr;
  if (!encode) {
    cudaFuncSetAttribute(attn_kernel, cudaFuncAttributeMaxDynamicSharedMemorySize, SMEM_BYTES);
    void* fn = nullptr;
    cudaDriverEntryPointQueryResult qres;
    cudaGetDriverEntryPoint("cuTensorMapEncodeTiled", &fn, cudaEnableDefault, &qres);
    encode = (EncodeTiledFn)fn;
  }
  CUtensorMap tmq;
  {
    const cuuint64_t dims[2] = {(cuuint64_t)DH, (cuuint64_t)HQ * SQ};
    const cuuint64_t strides[1] = {(cuuint64_t)DH * 2};
    const cuuint32_t box[2] = {64, QROWS};
    const cuuint32_t estr[2] = {1, 1};
    encode(&tmq, CU_TENSOR_MAP_DATA_TYPE_BFLOAT16, 2, d_in[0], dims, strides, box, estr, CU_TENSOR_MAP_INTERLEAVE_NONE, CU_TENSOR_MAP_SWIZZLE_128B,
           CU_TENSOR_MAP_L2_PROMOTION_L2_256B, CU_TENSOR_MAP_FLOAT_OOB_FILL_NONE);
  }
  dequant_kernel<<<(2 * HKV * SKV) / (8 * 4), 256>>>(qk, qv, ks, kz, vs, vz);
  attn_kernel<<<NCTAS, 384, SMEM_BYTES>>>(tmq, (const __nv_bfloat16*)d_in[0], out, 0u);
}
```

```cpp
#include <cuda_runtime.h>
#include <cuda.h>
#include <cuda_bf16.h>
#include <stdint.h>

namespace {

constexpr int HQ = 32, HKV = 4, SQ = 2048, SKV = 2048, DH = 128;
constexpr int BN = 128;
constexpr int NBLK = SKV / BN;
constexpr int TILE_BYTES = BN * DH * 2;
constexpr int HALF_BYTES = TILE_BYTES / 2;
#define NK_STAGES 3
#ifndef NV_STAGES
#define NV_STAGES 3
#endif
constexpr int NK = NK_STAGES, NV = NV_STAGES;
constexpr int TILES_PER_CTA = 4;
#define CL 2
constexpr int NCTAS = 128;
#define QROWS 32
#define QSLEEP 800
constexpr int QP = 2 * 128 / QROWS;
constexpr int SLICE = (SKV / SKV) * 32768 / CL;
constexpr int SMEM_BYTES = (NK + NV + 1) * TILE_BYTES + 1024 + 256;

constexpr size_t HEAD_STRIDE = 2u << 20, CNT_OFF = 1u << 20;
constexpr int SLICES = 32;
__device__ __align__(1024) uint8_t g_scratch[(HKV + 1) * HEAD_STRIDE];
__device__ __forceinline__ uint8_t* tile_img(uint8_t* scr, int h, int isV, int blk) { return scr + h * HEAD_STRIDE + (size_t)(2 * blk + isV) * TILE_BYTES; }
__device__ __forceinline__ unsigned* tile_cnt(uint8_t* scr, int h, int isV, int blk) { return reinterpret_cast<unsigned*>(scr + h * HEAD_STRIDE + CNT_OFF) + (2 * blk + isV) * 32; }

#define TS(e)

__device__ __forceinline__ uint32_t smem_u32(const void* p) { return (uint32_t)__cvta_generic_to_shared(p); }
__device__ __forceinline__ void wg_fence() { asm volatile("wgmma.fence.sync.aligned;\n" ::: "memory"); }
__device__ __forceinline__ void wg_commit() { asm volatile("wgmma.commit_group.sync.aligned;\n" ::: "memory"); }
template <int N> __device__ __forceinline__ void wg_wait() { asm volatile("wgmma.wait_group.sync.aligned %0;\n" ::"n"(N) : "memory"); }
template <int NR> __device__ __forceinline__ void fence_regs(float (&d)[NR]) {
#pragma unroll
  for (int i = 0; i < NR; i++) asm volatile("" : "+f"(d[i])::"memory");
}
template <int NR> __device__ __forceinline__ void fence_regs(uint32_t (&d)[NR]) {
#pragma unroll
  for (int i = 0; i < NR; i++) asm volatile("" : "+r"(d[i])::"memory");
}
__device__ __forceinline__ void bar_sync(int id, int n) { asm volatile("bar.sync %0, %1;\n" ::"r"(id), "r"(n) : "memory"); }
__device__ __forceinline__ void bar_arrive(int id, int n) { asm volatile("bar.arrive %0, %1;\n" ::"r"(id), "r"(n) : "memory"); }
__device__ __forceinline__ void bar_sync_sel(uint32_t second) {
  asm volatile("{\n.reg .pred p;\nsetp.ne.u32 p, %0, 0;\n@!p bar.sync 1, 256;\n@p bar.sync 2, 256;\n}\n" ::"r"(second) : "memory");
}
__device__ __forceinline__ void bar_arrive_sel(uint32_t second) {
  asm volatile("{\n.reg .pred p;\nsetp.ne.u32 p, %0, 0;\n@!p bar.arrive 1, 256;\n@p bar.arrive 2, 256;\n}\n" ::"r"(second) : "memory");
}
__device__ __forceinline__ void mbar_init(uint32_t bar, uint32_t count) {
  asm volatile("mbarrier.init.shared::cta.b64 [%0], %1;\n" ::"r"(bar), "r"(count) : "memory");
}
__device__ __forceinline__ void mbar_expect_tx(uint32_t bar, uint32_t bytes) {
  asm volatile("mbarrier.arrive.expect_tx.shared::cta.b64 _, [%0], %1;\n" ::"r"(bar), "r"(bytes) : "memory");
}
__device__ __forceinline__ void mbar_wait(uint32_t bar, uint32_t parity) {
  asm volatile(
      "{\n.reg .pred p;\n"
      "WAIT_LOOP:\n"
      "mbarrier.try_wait.parity.shared::cta.b64 p, [%0], %1;\n"
      "@p bra WAIT_DONE;\n"
      "bra WAIT_LOOP;\n"
      "WAIT_DONE:\n}\n" ::"r"(bar), "r"(parity) : "memory");
}
__device__ __forceinline__ uint32_t mbar_test(uint32_t bar, uint32_t parity) {
  uint32_t ok;
  asm volatile("{\n.reg .pred p;\nmbarrier.test_wait.parity.shared::cta.b64 p, [%1], %2;\nselp.u32 %0, 1, 0, p;\n}\n" : "=r"(ok) : "r"(bar), "r"(parity) : "memory");
  return ok;
}
__device__ __forceinline__ void mma_16816(float& c0, float& c1, float& c2, float& c3, uint32_t a0, uint32_t a1, uint32_t a2, uint32_t a3, uint32_t b0, uint32_t b1) {
  asm volatile("mma.sync.aligned.m16n8k16.row.col.f32.bf16.bf16.f32 {%0, %1, %2, %3}, {%4, %5, %6, %7}, {%8, %9}, {%0, %1, %2, %3};\n"
               : "+f"(c0), "+f"(c1), "+f"(c2), "+f"(c3) : "r"(a0), "r"(a1), "r"(a2), "r"(a3), "r"(b0), "r"(b1));
}
__device__ __forceinline__ float rcp_fast(float x) {
  float y;
  asm("rcp.approx.ftz.f32 %0, %1;\n" : "=f"(y) : "f"(x));
  return y;
}
__device__ __forceinline__ void mbar_arrive_local(uint32_t bar) {
  asm volatile("mbarrier.arrive.shared::cta.b64 _, [%0];\n" ::"r"(bar) : "memory");
}
__device__ __forceinline__ void mbar_arrive_cluster(uint32_t bar, uint32_t cta) {
  asm volatile(
      "{\n.reg .b32 ra;\n"
      "mapa.shared::cluster.u32 ra, %0, %1;\n"
      "mbarrier.arrive.shared::cluster.b64 _, [ra];\n}\n" ::"r"(bar), "r"(cta) : "memory");
}
__device__ __forceinline__ void bulk_load_mc(uint32_t dst, const void* src, uint32_t bytes, uint32_t bar, uint16_t mask) {
  asm volatile(
      "cp.async.bulk.shared::cluster.global.mbarrier::complete_tx::bytes.multicast::cluster [%0], [%1], %2, [%3], %4;\n" ::"r"(dst),
      "l"(src), "r"(bytes), "r"(bar), "h"(mask)
      : "memory");
}
__device__ __forceinline__ void bulk_load(uint32_t dst, const void* src, uint32_t bytes, uint32_t bar) {
  asm volatile("cp.async.bulk.shared::cluster.global.mbarrier::complete_tx::bytes [%0], [%1], %2, [%3];\n" ::"r"(dst), "l"(src),
               "r"(bytes), "r"(bar)
               : "memory");
}
__device__ __forceinline__ void tma_load_2d(uint32_t dst, const void* tmap, int c0, int c1, uint32_t bar) {
  asm volatile("cp.async.bulk.tensor.2d.shared::cluster.global.mbarrier::complete_tx::bytes [%0], [%1, {%3, %4}], [%2];\n" ::"r"(dst), "l"(tmap),
               "r"(bar), "r"(c0), "r"(c1)
               : "memory");
}
__device__ __forceinline__ void ldsm_x4(uint32_t& r0, uint32_t& r1, uint32_t& r2, uint32_t& r3, uint32_t addr) {
  asm volatile("ldmatrix.sync.aligned.m8n8.x4.shared.b16 {%0, %1, %2, %3}, [%4];\n" : "=r"(r0), "=r"(r1), "=r"(r2), "=r"(r3) : "r"(addr) : "memory");
}
__device__ __forceinline__ bool wg_any(bool p, int id) {
  uint32_t r;
  asm volatile("{\n.reg .pred p, q;\nsetp.ne.u32 p, %1, 0;\nbarrier.cta.red.or.aligned.pred q, %2, 128, p;\nselp.u32 %0, 1, 0, q;\n}\n"
               : "=r"(r) : "r"((uint32_t)p), "r"(id) : "memory");
  return r != 0;
}
__device__ __forceinline__ float ex2(float x) {
  float y;
  asm("ex2.approx.ftz.f32 %0, %1;\n" : "=f"(y) : "f"(x));
  return y;
}
__device__ __forceinline__ uint32_t pack_bf16(float lo, float hi) {
  uint32_t r;
  asm("cvt.rn.bf16x2.f32 %0, %1, %2;\n" : "=r"(r) : "f"(hi), "f"(lo));
  return r;
}
__device__ __forceinline__ uint64_t make_desc(uint32_t addr, uint32_t lbo, uint32_t sbo) {
  return (uint64_t)((addr & 0x3FFFF) >> 4) | ((uint64_t)(lbo >> 4) << 16) | ((uint64_t)(sbo >> 4) << 32) | (1ull << 62);
}

__device__ __forceinline__ void wgmma_rs_kmaj(float (&d)[64], uint32_t a0, uint32_t a1, uint32_t a2, uint32_t a3, uint64_t descB, int scaleD) {
  asm volatile("{\n.reg .pred p;\nsetp.ne.b32 p, %69, 0;\n"
    "wgmma.mma_async.sync.aligned.m64n128k16.f32.bf16.bf16 "
    "{%0, %1, %2, %3, %4, %5, %6, %7, %8, %9, %10, %11, %12, %13, %14, %15, "
    "%16, %17, %18, %19, %20, %21, %22, %23, %24, %25, %26, %27, %28, %29, %30, %31, "
    "%32, %33, %34, %35, %36, %37, %38, %39, %40, %41, %42, %43, %44, %45, %46, %47, "
    "%48, %49, %50, %51, %52, %53, %54, %55, %56, %57, %58, %59, %60, %61, %62, %63}, "
    "{%64, %65, %66, %67}, %68, p, 1, 1, 0;\n}\n"
    : "+f"(d[0]), "+f"(d[1]), "+f"(d[2]), "+f"(d[3]), "+f"(d[4]), "+f"(d[5]), "+f"(d[6]), "+f"(d[7]),
      "+f"(d[8]), "+f"(d[9]), "+f"(d[10]), "+f"(d[11]), "+f"(d[12]), "+f"(d[13]), "+f"(d[14]), "+f"(d[15]),
      "+f"(d[16]), "+f"(d[17]), "+f"(d[18]), "+f"(d[19]), "+f"(d[20]), "+f"(d[21]), "+f"(d[22]), "+f"(d[23]),
      "+f"(d[24]), "+f"(d[25]), "+f"(d[26]), "+f"(d[27]), "+f"(d[28]), "+f"(d[29]), "+f"(d[30]), "+f"(d[31]),
      "+f"(d[32]), "+f"(d[33]), "+f"(d[34]), "+f"(d[35]), "+f"(d[36]), "+f"(d[37]), "+f"(d[38]), "+f"(d[39]),
      "+f"(d[40]), "+f"(d[41]), "+f"(d[42]), "+f"(d[43]), "+f"(d[44]), "+f"(d[45]), "+f"(d[46]), "+f"(d[47]),
      "+f"(d[48]), "+f"(d[49]), "+f"(d[50]), "+f"(d[51]), "+f"(d[52]), "+f"(d[53]), "+f"(d[54]), "+f"(d[55]),
      "+f"(d[56]), "+f"(d[57]), "+f"(d[58]), "+f"(d[59]), "+f"(d[60]), "+f"(d[61]), "+f"(d[62]), "+f"(d[63])
    : "r"(a0), "r"(a1), "r"(a2), "r"(a3), "l"(descB), "r"(scaleD));
}

__device__ __forceinline__ void wgmma_ss_kmaj(float (&d)[64], uint64_t descA, uint64_t descB, int scaleD) {
  asm volatile("{\n.reg .pred p;\nsetp.ne.b32 p, %66, 0;\n"
    "wgmma.mma_async.sync.aligned.m64n128k16.f32.bf16.bf16 "
    "{%0, %1, %2, %3, %4, %5, %6, %7, %8, %9, %10, %11, %12, %13, %14, %15, "
    "%16, %17, %18, %19, %20, %21, %22, %23, %24, %25, %26, %27, %28, %29, %30, %31, "
    "%32, %33, %34, %35, %36, %37, %38, %39, %40, %41, %42, %43, %44, %45, %46, %47, "
    "%48, %49, %50, %51, %52, %53, %54, %55, %56, %57, %58, %59, %60, %61, %62, %63}, "
    "%64, %65, p, 1, 1, 0, 0;\n}\n"
    : "+f"(d[0]), "+f"(d[1]), "+f"(d[2]), "+f"(d[3]), "+f"(d[4]), "+f"(d[5]), "+f"(d[6]), "+f"(d[7]),
      "+f"(d[8]), "+f"(d[9]), "+f"(d[10]), "+f"(d[11]), "+f"(d[12]), "+f"(d[13]), "+f"(d[14]), "+f"(d[15]),
      "+f"(d[16]), "+f"(d[17]), "+f"(d[18]), "+f"(d[19]), "+f"(d[20]), "+f"(d[21]), "+f"(d[22]), "+f"(d[23]),
      "+f"(d[24]), "+f"(d[25]), "+f"(d[26]), "+f"(d[27]), "+f"(d[28]), "+f"(d[29]), "+f"(d[30]), "+f"(d[31]),
      "+f"(d[32]), "+f"(d[33]), "+f"(d[34]), "+f"(d[35]), "+f"(d[36]), "+f"(d[37]), "+f"(d[38]), "+f"(d[39]),
      "+f"(d[40]), "+f"(d[41]), "+f"(d[42]), "+f"(d[43]), "+f"(d[44]), "+f"(d[45]), "+f"(d[46]), "+f"(d[47]),
      "+f"(d[48]), "+f"(d[49]), "+f"(d[50]), "+f"(d[51]), "+f"(d[52]), "+f"(d[53]), "+f"(d[54]), "+f"(d[55]),
      "+f"(d[56]), "+f"(d[57]), "+f"(d[58]), "+f"(d[59]), "+f"(d[60]), "+f"(d[61]), "+f"(d[62]), "+f"(d[63])
    : "l"(descA), "l"(descB), "r"(scaleD));
}

__device__ __forceinline__ void wgmma_rs_nmaj(float (&d)[64], uint32_t a0, uint32_t a1, uint32_t a2, uint32_t a3, uint64_t descB, int scaleD) {
  asm volatile("{\n.reg .pred p;\nsetp.ne.b32 p, %69, 0;\n"
    "wgmma.mma_async.sync.aligned.m64n128k16.f32.bf16.bf16 "
    "{%0, %1, %2, %3, %4, %5, %6, %7, %8, %9, %10, %11, %12, %13, %14, %15, "
    "%16, %17, %18, %19, %20, %21, %22, %23, %24, %25, %26, %27, %28, %29, %30, %31, "
    "%32, %33, %34, %35, %36, %37, %38, %39, %40, %41, %42, %43, %44, %45, %46, %47, "
    "%48, %49, %50, %51, %52, %53, %54, %55, %56, %57, %58, %59, %60, %61, %62, %63}, "
    "{%64, %65, %66, %67}, %68, p, 1, 1, 1;\n}\n"
    : "+f"(d[0]), "+f"(d[1]), "+f"(d[2]), "+f"(d[3]), "+f"(d[4]), "+f"(d[5]), "+f"(d[6]), "+f"(d[7]),
      "+f"(d[8]), "+f"(d[9]), "+f"(d[10]), "+f"(d[11]), "+f"(d[12]), "+f"(d[13]), "+f"(d[14]), "+f"(d[15]),
      "+f"(d[16]), "+f"(d[17]), "+f"(d[18]), "+f"(d[19]), "+f"(d[20]), "+f"(d[21]), "+f"(d[22]), "+f"(d[23]),
      "+f"(d[24]), "+f"(d[25]), "+f"(d[26]), "+f"(d[27]), "+f"(d[28]), "+f"(d[29]), "+f"(d[30]), "+f"(d[31]),
      "+f"(d[32]), "+f"(d[33]), "+f"(d[34]), "+f"(d[35]), "+f"(d[36]), "+f"(d[37]), "+f"(d[38]), "+f"(d[39]),
      "+f"(d[40]), "+f"(d[41]), "+f"(d[42]), "+f"(d[43]), "+f"(d[44]), "+f"(d[45]), "+f"(d[46]), "+f"(d[47]),
      "+f"(d[48]), "+f"(d[49]), "+f"(d[50]), "+f"(d[51]), "+f"(d[52]), "+f"(d[53]), "+f"(d[54]), "+f"(d[55]),
      "+f"(d[56]), "+f"(d[57]), "+f"(d[58]), "+f"(d[59]), "+f"(d[60]), "+f"(d[61]), "+f"(d[62]), "+f"(d[63])
    : "r"(a0), "r"(a1), "r"(a2), "r"(a3), "l"(descB), "r"(scaleD));
}

struct DqCtx { const int* qk; const int* qv; const __nv_bfloat16 *ks, *kz, *vs, *vz; uint8_t* scr; };
__device__ __forceinline__ float bf_lo(uint32_t u) { return __uint_as_float(u << 16); }
__device__ __forceinline__ float bf_hi(uint32_t u) { return __uint_as_float(u & 0xffff0000u); }
__device__ __forceinline__ float bf_round(float x) { return __bfloat162float(__float2bfloat16_rn(x)); }
__device__ __forceinline__ uint32_t dq_pair_small(int a, int b, uint32_t z2, uint32_t s2) {
  uint32_t v = __byte_perm(a, b, 0x5410) | 0x43004300u, r;
  asm("{\n.reg .b32 x, d;\n"
      "sub.rn.bf16x2 x, %1, %4;\n"
      "sub.rn.bf16x2 d, x, %2;\n"
      "mul.rn.bf16x2 %0, d, %3;\n}\n" : "=r"(r) : "r"(v), "r"(z2), "r"(s2), "r"(0x43004300u));
  return r;
}
__device__ __forceinline__ uint32_t dq_pair_any(int a, int b, uint32_t z2, uint32_t s2) {
  return pack_bf16(bf_round(bf_round((float)a) - bf_lo(z2)) * bf_lo(s2), bf_round(bf_round((float)b) - bf_hi(z2)) * bf_hi(s2));
}
struct DqLane {
  int off, ch; bool odd;
  __device__ __forceinline__ DqLane(bool isV, int lane) {
    const int J = lane >> 3, c = (lane & 7) >> 1, sb = lane & 1, j = 4 * J + 2 * sb + (c & 1);
    const int half = isV ? j >> 3 : lane >> 4, sub = isV ? c >> 1 : lane & 1;
    ch = isV ? j & 7 : (lane >> 1) & 7;
    off = half * HALF_BYTES + sub * 8;
    odd = c & 1;
  }
};
__device__ __forceinline__ void dq_put(bool isV, const DqLane& L, uint8_t* img, int rr, uint32_t p0, uint32_t p1) {
  uint2 w;
  if (isV) {
    const uint32_t recv = __shfl_xor_sync(0xffffffffu, L.odd ? p0 : p1, 2);
    if (L.odd) { w.x = recv; w.y = p1; } else { w.x = p0; w.y = recv; }
  } else { w.x = p0; w.y = p1; }
  *reinterpret_cast<uint2*>(img + L.off + rr * 128 + ((L.ch ^ (rr & 7)) << 4)) = w;
}
__device__ __noinline__ void dq_rows_any(const DqCtx d, bool isV, int r0, int n, int lane, uint8_t* img) {
  const DqLane L(isV, lane);
  for (int r = r0; r < r0 + n; r++) {
    const int4 x = *reinterpret_cast<const int4*>((isV ? d.qv : d.qk) + (size_t)r * DH + lane * 4);
    uint32_t za, zb, sa, sb;
    if (isV) {
      za = zb = (uint32_t)__bfloat16_as_ushort(d.vz[r]) * 0x10001u; sa = sb = (uint32_t)__bfloat16_as_ushort(d.vs[r]) * 0x10001u;
    } else {
      const uint2 zz = *reinterpret_cast<const uint2*>(d.kz + (size_t)(r / BN) * DH + lane * 4), ss = *reinterpret_cast<const uint2*>(d.ks + (size_t)(r / BN) * DH + lane * 4);
      za = zz.x; zb = zz.y; sa = ss.x; sb = ss.y;
    }
    dq_put(isV, L, img, r & (BN - 1), dq_pair_any(x.x, x.y, za, sa), dq_pair_any(x.z, x.w, zb, sb));
  }
}
template <int R> struct DqRows {
  int4 x[R];
  uint32_t z[R / 2], s[R / 2];
  __device__ __forceinline__ void load(const DqCtx& d, bool isV, int r0, int lane) {
    const int* src = (isV ? d.qv : d.qk) + (size_t)r0 * DH + lane * 4;
#pragma unroll
    for (int i = 0; i < R; i++) x[i] = __ldcs(reinterpret_cast<const int4*>(src + i * DH));
    const size_t o = isV ? (size_t)r0 : (size_t)(r0 / BN) * DH + lane * 4;
    const uint32_t* zp = reinterpret_cast<const uint32_t*>((isV ? d.vz : d.kz) + o);
    const uint32_t* sp = reinterpret_cast<const uint32_t*>((isV ? d.vs : d.ks) + o);
#pragma unroll
    for (int i = 0; i < R / 2; i += 2) {
      if (i == 0 || isV) {
        const uint2 zz = *reinterpret_cast<const uint2*>(zp + i), ss = *reinterpret_cast<const uint2*>(sp + i);
        z[i] = zz.x; z[i + 1] = zz.y; s[i] = ss.x; s[i + 1] = ss.y;
      }
    }
  }
  template <bool isV> __device__ __forceinline__ void store(const DqCtx& d, int r0, int lane) const {
    uint32_t any = 0;
#pragma unroll
    for (int i = 0; i < R; i++) any |= x[i].x | x[i].y | x[i].z | x[i].w;
    uint8_t* img = tile_img(d.scr, r0 / SKV, isV, (r0 / BN) & (NBLK - 1));
    if (!__all_sync(0xffffffffu, any < 128u)) { dq_rows_any(d, isV, r0, R, lane, img); return; }
    const DqLane L(isV, lane);
    const int rr0 = r0 & (BN - 1);
#pragma unroll
    for (int i = 0; i < R; i++) {
      uint32_t za, zb, sa, sb;
      if (isV) {
        za = zb = __byte_perm(z[i >> 1], 0, (i & 1) ? 0x3232 : 0x1010);
        sa = sb = __byte_perm(s[i >> 1], 0, (i & 1) ? 0x3232 : 0x1010);
      } else { za = z[0]; zb = z[1]; sa = s[0]; sb = s[1]; }
      dq_put(isV, L, img, rr0 + i, dq_pair_small(x[i].x, x[i].y, za, sa), dq_pair_small(x[i].z, x[i].w, zb, sb));
    }
  }
};
__device__ __forceinline__ void dq_publish(unsigned* cnt, int lane, unsigned n) {
  asm volatile("fence.proxy.async.global;\n" ::: "memory");
  __syncwarp();
  if (lane == 0) asm volatile("red.release.gpu.global.add.u32 [%0], %1;\n" ::"l"(cnt), "r"(n) : "memory");
}
__device__ __forceinline__ void dq_wait(const unsigned* cnt) {
  unsigned v, n = 0;
  while (true) {
    asm volatile("ld.acquire.gpu.global.u32 %0, [%1];\n" : "=r"(v) : "l"(cnt) : "memory");
    if (v >= SLICES) break;
    if (++n > (1u << 24)) __trap();
  }
  asm volatile("fence.proxy.async.global;\n" ::: "memory");
}
constexpr int NA = 12;
__device__ __forceinline__ int seq_isv(int u) { return u == 2 * NBLK - 1 || (u > 0 && !(u & 1)); }
__device__ __forceinline__ int seq_blk(int u) { return u == 2 * NBLK - 1 ? NBLK - 1 : ((u & 1) ? (u + 1) >> 1 : (u ? (u >> 1) - 1 : 0)); }
template <bool isV>
__device__ __forceinline__ void dq_stream(const DqCtx& dq, int h, int slice, int b0, int lane) {
  const int* src = (isV ? dq.qv : dq.qk) + (size_t)(h * SKV + b0 * BN + slice * 4) * DH + lane * 4;
  const __nv_bfloat16* zp = (isV ? dq.vz : dq.kz) + (isV ? h * SKV + b0 * BN + slice * 4 : (h * NBLK + b0) * DH + lane * 4);
  const ptrdiff_t sdiff = (isV ? dq.vs : dq.ks) - (isV ? dq.vz : dq.kz);
  uint8_t* img = tile_img(dq.scr, h, isV, b0);
  unsigned* cnt = tile_cnt(dq.scr, h, isV, b0);
  const DqLane L(isV, lane);
  const int rr0 = slice * 4;
  auto ld = [&](const int* p) { return __ldcs(reinterpret_cast<const int4*>(p)); };
  auto prefetch = [&](const int* p) { if (lane < 16) asm volatile("prefetch.global.L2 [%0];\n" ::"l"(p - lane * 4 + lane * 32)); };
  auto rows2 = [&](const int4 xa, const int4 xb, int i, const uint2 zz, const uint2 ss) {
    const uint32_t any = xa.x | xa.y | xa.z | xa.w | xb.x | xb.y | xb.z | xb.w;
    const uint32_t zw = i ? zz.y : zz.x, sw = i ? ss.y : ss.x;
    if (__all_sync(0xffffffffu, any < 128u)) {
      if (isV) {
        const uint32_t z0 = __byte_perm(zw, 0, 0x1010), s0 = __byte_perm(sw, 0, 0x1010), z1 = __byte_perm(zw, 0, 0x3232), s1 = __byte_perm(sw, 0, 0x3232);
        dq_put(true, L, img, rr0 + i, dq_pair_small(xa.x, xa.y, z0, s0), dq_pair_small(xa.z, xa.w, z0, s0));
        dq_put(true, L, img, rr0 + i + 1, dq_pair_small(xb.x, xb.y, z1, s1), dq_pair_small(xb.z, xb.w, z1, s1));
      } else {
        dq_put(false, L, img, rr0 + i, dq_pair_small(xa.x, xa.y, zz.x, ss.x), dq_pair_small(xa.z, xa.w, zz.y, ss.y));
        dq_put(false, L, img, rr0 + i + 1, dq_pair_small(xb.x, xb.y, zz.x, ss.x), dq_pair_small(xb.z, xb.w, zz.y, ss.y));
      }
    } else {
      int4 x = xa;
#pragma unroll 1
      for (int e = 0; e < 2; e++) {
        const uint32_t sel = e ? 0x3232 : 0x1010;
        const uint32_t za = isV ? __byte_perm(zw, 0, sel) : zz.x, zb = isV ? za : zz.y, sa = isV ? __byte_perm(sw, 0, sel) : ss.x, sb = isV ? sa : ss.y;
        dq_put(isV, L, img, rr0 + i + e, dq_pair_any(x.x, x.y, za, sa), dq_pair_any(x.z, x.w, zb, sb));
        x = xb;
      }
    }
  };
  prefetch(src + BN * DH);
  int4 xa = ld(src), xb = ld(src + DH);
  uint2 zz = *reinterpret_cast<const uint2*>(zp), ss = *reinterpret_cast<const uint2*>(zp + sdiff);
#pragma unroll 1
  for (int b = b0; b < NBLK; b++) {
    if (b + 2 < NBLK) prefetch(src + 2 * BN * DH);
    rows2(xa, xb, 0, zz, ss);
    xa = ld(src + 2 * DH); xb = ld(src + 3 * DH);
    rows2(xa, xb, 2, zz, ss);
    src += BN * DH; zp += isV ? BN : DH;
    if (b + 1 < NBLK) {
      xa = ld(src); xb = ld(src + DH);
      zz = *reinterpret_cast<const uint2*>(zp); ss = *reinterpret_cast<const uint2*>(zp + sdiff);
    }
    dq_publish(cnt, lane, 1);
    img += 2 * TILE_BYTES; cnt += 64;
  }
}

__global__ void __launch_bounds__(256) dequant_kernel(const int* __restrict__ qk, const int* __restrict__ qv,
                                                      const __nv_bfloat16* __restrict__ ks, const __nv_bfloat16* __restrict__ kz,
                                                      const __nv_bfloat16* __restrict__ vs, const __nv_bfloat16* __restrict__ vz, uint8_t* scr) {
  constexpr int ROWS_PER_WARP = 4;
  const int lane = threadIdx.x & 31;
  const int warp = blockIdx.x * 8 + (threadIdx.x >> 5);
  const int row0 = warp * ROWS_PER_WARP;
  const bool isV = row0 >= HKV * SKV;
  const int r0 = isV ? row0 - HKV * SKV : row0;
  const int* src = (isV ? qv : qk) + (size_t)r0 * DH + lane * 4;
  int4 x[ROWS_PER_WARP];
#pragma unroll
  for (int i = 0; i < ROWS_PER_WARP; i++) x[i] = __ldcs(reinterpret_cast<const int4*>(src + i * DH));
  float z[4], s[4];
  if (!isV) {
    const int g = r0 / BN;
    const uint2 zz = *reinterpret_cast<const uint2*>(kz + (size_t)g * DH + lane * 4);
    const uint2 ss = *reinterpret_cast<const uint2*>(ks + (size_t)g * DH + lane * 4);
    z[0] = __uint_as_float(zz.x << 16); z[1] = __uint_as_float(zz.x & 0xffff0000u);
    z[2] = __uint_as_float(zz.y << 16); z[3] = __uint_as_float(zz.y & 0xffff0000u);
    s[0] = __uint_as_float(ss.x << 16); s[1] = __uint_as_float(ss.x & 0xffff0000u);
    s[2] = __uint_as_float(ss.y << 16); s[3] = __uint_as_float(ss.y & 0xffff0000u);
  }
  uint8_t* img = tile_img(scr, r0 / SKV, isV, (r0 / BN) & (NBLK - 1));
  const int J = lane >> 3, c = (lane & 7) >> 1, sb = lane & 1;
  const int j = 4 * J + 2 * sb + (c & 1);
  const int half = j >> 3, ch = j & 7;
#pragma unroll
  for (int i = 0; i < ROWS_PER_WARP; i++) {
    const int r = r0 + i;
    if (isV) {
      const float zv = __bfloat162float(vz[r]), sv = __bfloat162float(vs[r]);
#pragma unroll
      for (int e = 0; e < 4; e++) { z[e] = zv; s[e] = sv; }
    }
    const int xi[4] = {x[i].x, x[i].y, x[i].z, x[i].w};
    float o[4];
#pragma unroll
    for (int e = 0; e < 4; e++) {
      const float qf = __bfloat162float(__float2bfloat16_rn((float)xi[e]));
      const float df = __bfloat162float(__float2bfloat16_rn(qf - z[e]));
      o[e] = df * s[e];
    }
    const uint32_t p0 = pack_bf16(o[0], o[1]), p1 = pack_bf16(o[2], o[3]);
    const int rr = r & (BN - 1);
    uint2 w;
    if (isV) {
      const uint32_t send = (c & 1) ? p0 : p1;
      const uint32_t recv = __shfl_xor_sync(0xffffffffu, send, 2);
      if (c & 1) { w.x = recv; w.y = p1; } else { w.x = p0; w.y = recv; }
      *reinterpret_cast<uint2*>(img + half * HALF_BYTES + rr * 128 + ((ch ^ (rr & 7)) << 4) + (c >> 1) * 8) = w;
    } else {
      w.x = p0; w.y = p1;
      *reinterpret_cast<uint2*>(img + (lane >> 4) * HALF_BYTES + rr * 128 + ((((lane >> 1) & 7) ^ (rr & 7)) << 4) + (lane & 1) * 8) = w;
    }
  }
}

constexpr float SCALE_LOG2 = 0.08838834764831845f * 1.4426950408889634f;
#define SPLIT 5
#define DEPD 2
constexpr float SUM_THR = 4294967296.0f;

__device__ __forceinline__ void issue_qk(float (&S)[64], const uint32_t (&Q)[32], uint32_t kaddr) {
  const uint64_t d0 = make_desc(kaddr, 16, 1024);
#pragma unroll
  for (int k = 0; k < 8; k++)
    wgmma_rs_kmaj(S, Q[4 * k], Q[4 * k + 1], Q[4 * k + 2], Q[4 * k + 3], d0 + (uint64_t)(((k & 3) * 32 + (k >> 2) * HALF_BYTES) >> 4), k != 0);
}
__device__ __forceinline__ void issue_qk_ss(float (&S)[64], uint32_t qaddr, uint32_t kaddr) {
  const uint64_t a0 = make_desc(qaddr, 16, 1024), d0 = make_desc(kaddr, 16, 1024);
#pragma unroll
  for (int k = 0; k < 8; k++) {
    const uint64_t off = (uint64_t)(((k & 3) * 32 + (k >> 2) * HALF_BYTES) >> 4);
    wgmma_ss_kmaj(S, a0 + off, d0 + off, k != 0);
  }
}
__device__ __forceinline__ void issue_pv(float (&O)[64], const uint32_t (&P)[32], uint32_t vaddr, int acc) {
  const uint64_t d0 = make_desc(vaddr, HALF_BYTES, 1024);
#pragma unroll
  for (int k = 0; k < 8; k++)
    wgmma_rs_nmaj(O, P[4 * k], P[4 * k + 1], P[4 * k + 2], P[4 * k + 3], d0 + (uint64_t)((k * 2048) >> 4), (k != 0) | acc);
}
__device__ __forceinline__ float tie(float a, float b, uint32_t z) {
  uint32_t r;
  asm("lop3.b32 %0, %1, %2, %3, 0xF8;\n" : "=r"(r) : "r"(__float_as_uint(a)), "r"(__float_as_uint(b)), "r"(z));
  return __uint_as_float(r);
}

__device__ __forceinline__ uint32_t tieu(uint32_t a, float b, uint32_t z) {
  uint32_t r;
  asm("lop3.b32 %0, %1, %2, %3, 0xF8;\n" : "=r"(r) : "r"(a), "r"(__float_as_uint(b)), "r"(z));
  return r;
}

#define BAR_SYNC_MINE bar_sync(my_bar, 256)
#define BAR_ARRIVE_OTHER bar_arrive(other_bar, 256)
#define LDSM_POS 0
template <bool B> struct BoolC { static constexpr bool value = B; };

__global__ void __cluster_dims__(CL, 1, 1) __launch_bounds__(384, 1)
attn_kernel(const __grid_constant__ CUtensorMap tmq, const __nv_bfloat16* __restrict__ q, __nv_bfloat16* __restrict__ out, const uint32_t zero,
            const DqCtx dq, const int fused) {
  extern __shared__ uint8_t smem_raw[];
  const uint32_t sbase = (smem_u32(smem_raw) + 1023u) & ~1023u;
  const uint32_t sK = sbase, sV = sbase + NK * TILE_BYTES, sQ = sbase + (NK + NV) * TILE_BYTES;
  const uint32_t bars = sbase + (NK + NV + 1) * TILE_BYTES;
  const uint32_t fullK = bars, fullV = bars + 8 * NK, emptyK = bars + 8 * (NK + NV), emptyV = emptyK + 8 * NK;
  const uint32_t fullQ = emptyV + 8 * NV, emptyQ = fullQ + 8, pollDone = emptyQ + 8;

  const int cta = blockIdx.x;
  const int warp = __shfl_sync(0xffffffffu, (int)(threadIdx.x >> 5), 0);
  const int lane = threadIdx.x & 31;
  const int wg = warp >> 2;
  const uint32_t rank = cta & (CL - 1);
  const int h = cta >> 5;
  const int row0 = cta * (TILES_PER_CTA * 128);

  const int isV0 = seq_isv(warp), blk0 = seq_blk(warp);
  const int r0 = h * SKV + blk0 * BN + (cta & (SLICES - 1)) * 4;
  DqRows<4> x0;
  uint4 q0[8];
  unsigned first_poll = SLICES;
  if (warp >= 4) {
    const __nv_bfloat16* qs = q + (size_t)(row0 + (warp - 4) * 16 + (lane >> 4)) * DH + (lane & 15) * 8;
#pragma unroll
    for (int i = 0; i < 8; i++) q0[i] = __ldcs(reinterpret_cast<const uint4*>(qs + 2 * i * DH));
  } else if (fused) {
    if (threadIdx.x == 96) asm volatile("ld.relaxed.gpu.global.u32 %0, [%1];\n" : "=r"(first_poll) : "l"(tile_cnt(dq.scr, h, 0, 0)) : "memory");
    x0.load(dq, isV0, r0, lane);
  }
  if (threadIdx.x == 0) {
    for (int s = 0; s < NK; s++) { mbar_init(fullK + 8 * s, 1); mbar_init(emptyK + 8 * s, 8 * CL); }
    for (int s = 0; s < NV; s++) { mbar_init(fullV + 8 * s, 1); mbar_init(emptyV + 8 * s, 8 * CL); }
    mbar_init(fullQ, 1); mbar_init(emptyQ, 8); mbar_init(pollDone, 1);
    asm volatile("fence.mbarrier_init.release.cluster;\n" ::: "memory");
  }
  asm volatile("barrier.cluster.arrive.relaxed.aligned;\n" ::: "memory");
  if (warp >= 4) {
#pragma unroll
    for (int i = 0; i < 8; i++) {
      const int rr = (warp - 4) * 16 + 2 * i + (lane >> 4);
      asm volatile("st.shared.v4.b32 [%0], {%1, %2, %3, %4};\n" ::"r"(sQ + ((lane >> 3) & 1) * HALF_BYTES + rr * 128 + (((lane ^ rr) & 7) << 4)),
                   "r"(q0[i].x), "r"(q0[i].y), "r"(q0[i].z), "r"(q0[i].w) : "memory");
    }
    asm volatile("fence.proxy.async.shared::cta;\n" ::: "memory");
    if (fused) x0.load(dq, isV0, r0, lane);
  }
  if (fused && warp < NA) {
    if (isV0) x0.store<true>(dq, r0, lane); else x0.store<false>(dq, r0, lane);
    if (warp < 4) dq_publish(tile_cnt(dq.scr, h, isV0, blk0), lane, 1);
    else {
      asm volatile("fence.proxy.async.global;\n" ::: "memory");
      bar_arrive(9, 256 + 32);
    }
  }
  asm volatile("barrier.cluster.wait.aligned;\n" ::: "memory");

  constexpr int TOTAL = TILES_PER_CTA * NBLK;

  if (wg == 0) {
    asm volatile("setmaxnreg.dec.sync.aligned.u32 40;\n");
    if (warp == 3 && lane == 0) {
      const uint8_t* kimg = tile_img(dq.scr, h, 0, 0) + rank * SLICE;
      const uint8_t* vimg = tile_img(dq.scr, h, 1, 0) + rank * SLICE;
      int ks = 0, kph = 1, vs = 0, vph = 1;
      for (int i = 0; i <= TOTAL; i++) {
        if (i < TOTAL) {
          mbar_wait(emptyK + 8 * ks, kph);
          if (fused && i < NBLK) { if (i > 0 || first_poll < SLICES) dq_wait(tile_cnt(dq.scr, h, 0, i)); else asm volatile("fence.acq_rel.gpu;\nfence.proxy.async.global;\n" ::: "memory"); }
          mbar_expect_tx(fullK + 8 * ks, TILE_BYTES);
          bulk_load_mc(sK + ks * TILE_BYTES + rank * SLICE, kimg + (size_t)(i & (NBLK - 1)) * (2 * TILE_BYTES), SLICE, fullK + 8 * ks, (uint16_t)((1 << CL) - 1));
          if (++ks == NK) { ks = 0; kph ^= 1; }
        }
        if (i > 0) {
          mbar_wait(emptyV + 8 * vs, vph);
          if (fused && i <= NBLK) dq_wait(tile_cnt(dq.scr, h, 1, i - 1));
          if (i == NBLK) mbar_arrive_local(pollDone);
          mbar_expect_tx(fullV + 8 * vs, TILE_BYTES);
          bulk_load_mc(sV + vs * TILE_BYTES + rank * SLICE, vimg + (size_t)((i - 1) & (NBLK - 1)) * (2 * TILE_BYTES), SLICE, fullV + 8 * vs, (uint16_t)((1 << CL) - 1));
          if (++vs == NV) { vs = 0; vph ^= 1; }
        }
      }
    } else if (warp == 0 && fused) {
      bar_sync(9, 256 + 32);
      if (lane < 8) asm volatile("red.release.gpu.global.add.u32 [%0], 1;\n" ::"l"(tile_cnt(dq.scr, h, seq_isv(4 + lane), seq_blk(4 + lane))) : "memory");
      dq_stream<false>(dq, h, cta & (SLICES - 1), 7, lane);
      if (lane == 0) {
        mbar_wait(pollDone, 0);
        unsigned* done = reinterpret_cast<unsigned*>(dq.scr + CNT_OFF) + 2 * NBLK * 32;
        if (atomicAdd(done, 1u) == NCTAS - 1) {
          for (int k = 0; k < HKV * 2 * NBLK; k++) *tile_cnt(dq.scr, k / (2 * NBLK), k & 1, (k >> 1) & (NBLK - 1)) = 0;
          *done = 0;
        }
      }
    } else if (warp == 1 && fused) {
      dq_stream<true>(dq, h, cta & (SLICES - 1), 5, lane);
    } else if (warp == 2 && lane == 0) {
      for (int t = 1; t < TILES_PER_CTA; t++) {
        mbar_wait(emptyQ, (t & 1) ^ 1);
        mbar_expect_tx(fullQ, TILE_BYTES);
        for (int p = 0; p < QP; p++) {
          tma_load_2d(sQ + (p & 1) * HALF_BYTES + (p >> 1) * (QROWS * 128), &tmq, (p & 1) * 64, row0 + t * 128 + (p >> 1) * QROWS, fullQ);
          __nanosleep(QSLEEP);
        }
      }
    }
  } else {
    asm volatile("setmaxnreg.inc.sync.aligned.u32 232;\n");
    uint32_t tid;
    asm volatile("mov.u32 %0, %%tid.x;\n" : "=r"(tid));
    const int my_bar = tid >> 7, other_bar = 3 - my_bar;
    const int cw = my_bar - 1;
    const int wq = (tid >> 5) & 3;
    const int c = lane & 3;
    const int myrow = row0 + cw * 64 + wq * 16 + (lane >> 2);
    __nv_bfloat16* optr = out + (size_t)myrow * DH + 8 * c;
    const uint32_t qaddr = sQ + (cw * 64 + wq * 16 + (lane & 15)) * 128 + ((((lane >> 4) ^ lane) & 7) << 4);

    float S[64], O[64];
    uint32_t P[32], Q[32];
    float m0, m1, l0 = 0.f, l1 = 0.f;
    float s0, s1;
#pragma unroll
    for (int i = 0; i < 64; i++) { S[i] = 0.f; O[i] = 0.f; }

    auto ldsm_q = [&]() {
#pragma unroll
      for (int k = 0; k < 8; k++) ldsm_x4(Q[4 * k], Q[4 * k + 1], Q[4 * k + 2], Q[4 * k + 3], (qaddr ^ ((k & 3) << 5)) + (k >> 2) * HALF_BYTES);
    };
    auto release = [&](uint32_t bar) {
      if (lane < CL) mbar_arrive_cluster(bar, lane);
    };
    auto exps = [&](int k0, int k1, float b0, float b1, float (&hist)[8][2]) {
#pragma unroll
      for (int k = 0; k < 8; k++) {
        if (k >= k0 && k < k1) {
          float c0 = b0, c1 = b1;
          if (k - DEPD >= 0) { c0 = tie(b0, hist[k - DEPD][0], zero); c1 = tie(b1, hist[k - DEPD][1], zero); }
          float a0 = k ? hist[k - 1][0] : 0.f, a1 = k ? hist[k - 1][1] : 0.f;
#pragma unroll
          for (int j = 2 * k; j < 2 * k + 2; j++) {
            S[4 * j + 0] = ex2(fmaf(S[4 * j + 0], SCALE_LOG2, c0));
            S[4 * j + 1] = ex2(fmaf(S[4 * j + 1], SCALE_LOG2, c0));
            S[4 * j + 2] = ex2(fmaf(S[4 * j + 2], SCALE_LOG2, c1));
            S[4 * j + 3] = ex2(fmaf(S[4 * j + 3], SCALE_LOG2, c1));
            if (j == 0) { a0 = S[0] + S[1]; a1 = S[2] + S[3]; }
            else { a0 += S[4 * j + 0]; a0 += S[4 * j + 1]; a1 += S[4 * j + 2]; a1 += S[4 * j + 3]; }
          }
          hist[k][0] = a0; hist[k][1] = a1;
        }
      }
    };
    auto convert_p = [&]() {
#pragma unroll
      for (int i = 0; i < 32; i++) P[i] = pack_bf16(S[2 * i], S[2 * i + 1]);
    };
    auto redo_block = [&](uint32_t kaddr, int tile) {
      const uint32_t* qp = reinterpret_cast<const uint32_t*>(q + ((size_t)myrow + tile * 128) * DH) + c;
#pragma unroll
      for (int k = 0; k < 8; k++) {
        P[4 * k] = qp[8 * k]; P[4 * k + 1] = qp[8 * k + 4 * DH]; P[4 * k + 2] = qp[8 * k + 4]; P[4 * k + 3] = qp[8 * k + 4 + 4 * DH];
      }
      const uint32_t a0 = kaddr + (lane & 7) * 128 + ((((lane >> 3) ^ lane) & 7) << 4);
      float T[64];
      float x0 = m0, x1 = m1;
#pragma unroll 1
      for (int j = 0; j < 16; j++) {
        float c0 = 0.f, c1 = 0.f, c2 = 0.f, c3 = 0.f;
#pragma unroll
        for (int kq = 0; kq < 4; kq++) {
          uint32_t b0, b1, b2, b3;
          ldsm_x4(b0, b1, b2, b3, ((a0 ^ ((kq & 1) << 6)) + (kq >> 1) * HALF_BYTES + j * 1024));
          mma_16816(c0, c1, c2, c3, P[8 * kq], P[8 * kq + 1], P[8 * kq + 2], P[8 * kq + 3], b0, b1);
          mma_16816(c0, c1, c2, c3, P[8 * kq + 4], P[8 * kq + 5], P[8 * kq + 6], P[8 * kq + 7], b2, b3);
        }
        T[4 * j] = c0; T[4 * j + 1] = c1; T[4 * j + 2] = c2; T[4 * j + 3] = c3;
        x0 = fmaxf(x0, fmaxf(c0, c1)); x1 = fmaxf(x1, fmaxf(c2, c3));
      }
      x0 = fmaxf(x0, __shfl_xor_sync(0xffffffffu, x0, 1)); x1 = fmaxf(x1, __shfl_xor_sync(0xffffffffu, x1, 1));
      x0 = fmaxf(x0, __shfl_xor_sync(0xffffffffu, x0, 2)); x1 = fmaxf(x1, __shfl_xor_sync(0xffffffffu, x1, 2));
      const float a0f = ex2((m0 - x0) * SCALE_LOG2), a1f = ex2((m1 - x1) * SCALE_LOG2);
      m0 = x0; m1 = x1; l0 *= a0f; l1 *= a1f;
#pragma unroll
      for (int j = 0; j < 16; j++) { O[4 * j] *= a0f; O[4 * j + 1] *= a0f; O[4 * j + 2] *= a1f; O[4 * j + 3] *= a1f; }
      const float b0 = -m0 * SCALE_LOG2, b1 = -m1 * SCALE_LOG2;
      s0 = 0.f; s1 = 0.f;
      uint32_t U[32];
#pragma unroll 1
      for (int j = 0; j < 16; j++) {
        const float e0 = ex2(fmaf(T[4 * j], SCALE_LOG2, b0)), e1 = ex2(fmaf(T[4 * j + 1], SCALE_LOG2, b0));
        const float e2 = ex2(fmaf(T[4 * j + 2], SCALE_LOG2, b1)), e3 = ex2(fmaf(T[4 * j + 3], SCALE_LOG2, b1));
        s0 += e0 + e1; s1 += e2 + e3;
        U[2 * j] = pack_bf16(e0, e1); U[2 * j + 1] = pack_bf16(e2, e3);
      }
#pragma unroll
      for (int i = 0; i < 32; i++) P[i] = U[i];
    };
    auto pack_o = [&](float r0, float r1) {
#pragma unroll
      for (int J = 0; J < 4; J++) {
        float* o = &O[16 * J];
        asm volatile("{\n.reg .f32 t<16>;\n.reg .b32 u<8>;\n"
            "mul.f32 t0, %0, %16;\nmul.f32 t1, %1, %16;\nmul.f32 t2, %2, %17;\nmul.f32 t3, %3, %17;\n"
            "mul.f32 t4, %4, %16;\nmul.f32 t5, %5, %16;\nmul.f32 t6, %6, %17;\nmul.f32 t7, %7, %17;\n"
            "mul.f32 t8, %8, %16;\nmul.f32 t9, %9, %16;\nmul.f32 t10, %10, %17;\nmul.f32 t11, %11, %17;\n"
            "mul.f32 t12, %12, %16;\nmul.f32 t13, %13, %16;\nmul.f32 t14, %14, %17;\nmul.f32 t15, %15, %17;\n"
            "cvt.rn.bf16x2.f32 u0, t1, t0;\ncvt.rn.bf16x2.f32 u1, t5, t4;\ncvt.rn.bf16x2.f32 u2, t9, t8;\ncvt.rn.bf16x2.f32 u3, t13, t12;\n"
            "cvt.rn.bf16x2.f32 u4, t3, t2;\ncvt.rn.bf16x2.f32 u5, t7, t6;\ncvt.rn.bf16x2.f32 u6, t11, t10;\ncvt.rn.bf16x2.f32 u7, t15, t14;\n"
            "mov.b32 %0, u0;\nmov.b32 %1, u1;\nmov.b32 %2, u2;\nmov.b32 %3, u3;\n"
            "mov.b32 %4, u4;\nmov.b32 %5, u5;\nmov.b32 %6, u6;\nmov.b32 %7, u7;\n}\n"
            : "+f"(o[0]), "+f"(o[1]), "+f"(o[2]), "+f"(o[3]), "+f"(o[4]), "+f"(o[5]), "+f"(o[6]), "+f"(o[7]),
              "+f"(o[8]), "+f"(o[9]), "+f"(o[10]), "+f"(o[11]), "+f"(o[12]), "+f"(o[13]), "+f"(o[14]), "+f"(o[15])
            : "f"(r0), "f"(r1));
      }
    };
    auto store_o = [&](int tile) {
      __nv_bfloat16* o = optr + (size_t)tile * 128 * DH;
#pragma unroll
      for (int J = 0; J < 4; J++) {
        asm volatile("st.global.v4.b32 [%0], {%1, %2, %3, %4};\n" :: "l"(o + 32 * J), "f"(O[16 * J]), "f"(O[16 * J + 1]), "f"(O[16 * J + 2]), "f"(O[16 * J + 3]) : "memory");
        asm volatile("st.global.v4.b32 [%0], {%1, %2, %3, %4};\n" :: "l"(o + 8 * DH + 32 * J), "f"(O[16 * J + 4]), "f"(O[16 * J + 5]), "f"(O[16 * J + 6]), "f"(O[16 * J + 7]) : "memory");
      }
    };
#define EPI_MODE 1
#define STORE_AT_SETTLE store_o((i >> 4) - 1)
    auto settle = [&](int i, uint32_t kprev) {
      const int blk = i & (NBLK - 1);
      if (blk == 0) {
        if (i > 0) STORE_AT_SETTLE;
        l0 = 0.f; l1 = 0.f;
      }
      if (__any_sync(0xffffffffu, !(s0 <= SUM_THR) || !(s1 <= SUM_THR))) redo_block(kprev, i >> 4);
      l0 += s0; l1 += s1;
      if (blk == NBLK - 1) {
        l0 += __shfl_xor_sync(0xffffffffu, l0, 1); l1 += __shfl_xor_sync(0xffffffffu, l1, 1);
        l0 += __shfl_xor_sync(0xffffffffu, l0, 2); l1 += __shfl_xor_sync(0xffffffffu, l1, 2);
        l0 = rcp_fast(l0); l1 = rcp_fast(l1);
      }
    };

    int ks = 0, kph = 0, vs = 0, vph = 0;
    uint32_t kprev = sK, relKprev = emptyK;
    if (cw == 1) bar_arrive(1, 256);
    __syncwarp();
    ldsm_q();

    {
      mbar_wait(fullK, 0);
      BAR_SYNC_MINE;
      fence_regs(Q); fence_regs(S);
      wg_fence();
      issue_qk(S, Q, sK);
      wg_commit();
      BAR_ARRIVE_OTHER;
      if (lane == 0) mbar_arrive_local(emptyQ);
      ks = 1;
      wg_wait<0>();
      fence_regs(S);
      m0 = __shfl_sync(0xffffffffu, S[0], lane & ~3); m1 = __shfl_sync(0xffffffffu, S[2], lane & ~3);
      float hist[8][2];
      exps(0, 8, -m0 * SCALE_LOG2, -m1 * SCALE_LOG2, hist);
      convert_p();
      s0 = hist[7][0]; s1 = hist[7][1];
      mbar_wait(fullK + 8 * ks, kph);
      mbar_wait(fullV + 8 * vs, vph);
    }
    auto iteration = [&](auto pre_c, int i) {
      constexpr bool PRE = decltype(pre_c)::value;
      const int blk = PRE ? NBLK - 2 : (i & (NBLK - 1));
      const uint32_t kaddr = sK + ks * TILE_BYTES, vaddr = sV + vs * TILE_BYTES;
      const uint32_t relK = emptyK + 8 * ks, relV = emptyV + 8 * vs;
      if (++ks == NK) { ks = 0; kph ^= 1; }
      if (++vs == NV) { vs = 0; vph ^= 1; }
      const uint32_t nextK = fullK + 8 * ks, nextV = fullV + 8 * vs;
      BAR_SYNC_MINE;
      fence_regs(Q); fence_regs(S);
      wg_fence();
      issue_qk(S, Q, kaddr);
      wg_commit();
      settle(i, kprev);
      release(relKprev);
      kprev = kaddr; relKprev = relK;
      fence_regs(P); fence_regs(O);
      wg_fence();
      issue_pv(O, P, vaddr, blk != 0);
      wg_commit();
      BAR_ARRIVE_OTHER;
      if (PRE) mbar_wait(fullQ, (((i + 2) >> 4) & 1) ^ 1);
      else if (blk == NBLK - 1 && lane == 0) mbar_arrive_local(emptyQ);
      wg_wait<1>();
      fence_regs(S); fence_regs(Q);
      if (PRE) { if (LDSM_POS == 0) ldsm_q(); }
      else if (blk == NBLK - 1) { m0 = __shfl_sync(0xffffffffu, S[0], lane & ~3); m1 = __shfl_sync(0xffffffffu, S[2], lane & ~3); }
      const float b0 = -m0 * SCALE_LOG2, b1 = -m1 * SCALE_LOG2;
      float hist[8][2];
      exps(0, 8, b0, b1, hist);
      const uint32_t tK = mbar_test(nextK, tieu(kph, hist[SPLIT - 1][0], zero));
      const uint32_t tV = mbar_test(nextV, tieu(vph, hist[SPLIT - 1][1], zero));
      wg_wait<0>();
      const bool okK = __all_sync(0xffffffffu, tK) || (i + 2 >= TOTAL);
      const bool okV = __all_sync(0xffffffffu, tV);
      fence_regs(O); fence_regs(P);
      release(relV);
      convert_p();
      s0 = hist[7][0]; s1 = hist[7][1];
      if (PRE && LDSM_POS == 1) ldsm_q();
      if (!PRE && blk == NBLK - 1) {
        pack_o(l0, l1);
      }
      if (!okK) mbar_wait(nextK, kph);
      if (!okV) mbar_wait(nextV, vph);
    };
#pragma unroll 1
    for (int i = 0; i < TOTAL - 1; i++) {
      if ((i & (NBLK - 1)) == NBLK - 2 && i + 2 < TOTAL) iteration(BoolC<true>(), i);
      else iteration(BoolC<false>(), i);
    }
    {
      settle(TOTAL - 1, kprev);
      BAR_SYNC_MINE;
      fence_regs(P); fence_regs(O);
      wg_fence();
      issue_pv(O, P, sV + vs * TILE_BYTES, 1);
      wg_commit();
      BAR_ARRIVE_OTHER;
      wg_wait<0>();
      fence_regs(O);
      pack_o(l0, l1);
      store_o(TILES_PER_CTA - 1);
    }
    if (cw == 0) bar_sync(1, 256);
  }
  asm volatile("barrier.cluster.arrive.relaxed.aligned;\n" ::: "memory");
  asm volatile("barrier.cluster.wait.aligned;\n" ::: "memory");
}

}

typedef CUresult (*EncodeTiledFn)(CUtensorMap*, CUtensorMapDataType, cuuint32_t, void*, const cuuint64_t*, const cuuint64_t*, const cuuint32_t*,
                                  const cuuint32_t*, CUtensorMapInterleave, CUtensorMapSwizzle, CUtensorMapL2promotion, CUtensorMapFloatOOBfill);

extern "C" void kernel_launch(void* const* d_in, const int* in_sizes, int n_in, void* d_out, int out_size) {
  const int* qk = (const int*)d_in[1];
  const int* qv = (const int*)d_in[2];
  const __nv_bfloat16* ks = (const __nv_bfloat16*)d_in[3];
  const __nv_bfloat16* kz = (const __nv_bfloat16*)d_in[4];
  const __nv_bfloat16* vs = (const __nv_bfloat16*)d_in[5];
  const __nv_bfloat16* vz = (const __nv_bfloat16*)d_in[6];
  __nv_bfloat16* out = (__nv_bfloat16*)d_out;
  static EncodeTiledFn encode = nullptr;
  static int fused = 0;
  static uint8_t* scr = nullptr;
  if (!encode) {
    void* sp = nullptr;
    cudaGetSymbolAddress(&sp, g_scratch);
    scr = (uint8_t*)(((uintptr_t)sp + HEAD_STRIDE - 1) & ~(uintptr_t)(HEAD_STRIDE - 1));
    cudaFuncSetAttribute(attn_kernel, cudaFuncAttributeMaxDynamicSharedMemorySize, SMEM_BYTES);
    {
      cudaLaunchConfig_t cfg = {};
      cfg.gridDim = dim3(NCTAS); cfg.blockDim = dim3(384); cfg.dynamicSmemBytes = SMEM_BYTES;
      cudaLaunchAttribute at[1];
      at[0].id = cudaLaunchAttributeClusterDimension; at[0].val.clusterDim.x = CL; at[0].val.clusterDim.y = 1; at[0].val.clusterDim.z = 1;
      cfg.attrs = at; cfg.numAttrs = 1;
      int nc = 0;
      fused = cudaOccupancyMaxActiveClusters(&nc, attn_kernel, &cfg) == cudaSuccess && nc * CL >= NCTAS;
    }
    void* fn = nullptr;
    cudaDriverEntryPointQueryResult qres;
    cudaGetDriverEntryPoint("cuTensorMapEncodeTiled", &fn, cudaEnableDefault, &qres);
    encode = (EncodeTiledFn)fn;
  }
  CUtensorMap tmq;
  {
    const cuuint64_t dims[2] = {(cuuint64_t)DH, (cuuint64_t)HQ * SQ};
    const cuuint64_t strides[1] = {(cuuint64_t)DH * 2};
    const cuuint32_t box[2] = {64, QROWS};
    const cuuint32_t estr[2] = {1, 1};
    encode(&tmq, CU_TENSOR_MAP_DATA_TYPE_BFLOAT16, 2, d_in[0], dims, strides, box, estr, CU_TENSOR_MAP_INTERLEAVE_NONE, CU_TENSOR_MAP_SWIZZLE_128B,
           CU_TENSOR_MAP_L2_PROMOTION_L2_256B, CU_TENSOR_MAP_FLOAT_OOB_FILL_NONE);
  }
  const DqCtx dq = {qk, qv, ks, kz, vs, vz, scr};
  if (!fused) dequant_kernel<<<(2 * HKV * SKV) / (8 * 4), 256>>>(qk, qv, ks, kz, vs, vz, scr);
  attn_kernel<<<NCTAS, 384, SMEM_BYTES>>>(tmq, (const __nv_bfloat16*)d_in[0], out, 0u, dq, fused);
}
```

```cpp
#include <cuda_runtime.h>
#include <cuda.h>
#include <cuda_bf16.h>
#include <stdint.h>

namespace {

constexpr int HQ = 32, HKV = 4, SQ = 2048, SKV = 2048, DH = 128;
constexpr int BN = 128;
constexpr int NBLK = SKV / BN;
constexpr int TILE_BYTES = BN * DH * 2;
constexpr int HALF_BYTES = TILE_BYTES / 2;
#define NK_STAGES 3
#ifndef NV_STAGES
#define NV_STAGES 3
#endif
constexpr int NK = NK_STAGES, NV = NV_STAGES;
constexpr int TILES_PER_CTA = 4;
#define CL 2
constexpr int NCTAS = 128;
#define QROWS 32
#define QFIRST 2
constexpr int QP = 2 * 128 / QROWS;
constexpr int SLICE = (SKV / SKV) * 32768 / CL;
constexpr int SMEM_BYTES = (NK + NV + 1) * TILE_BYTES + 1024 + 256;

constexpr size_t HEAD_STRIDE = 2u << 20, CNT_OFF = 1u << 20;
constexpr int SLICES = 32;
__device__ __align__(1024) uint8_t g_scratch[(HKV + 1) * HEAD_STRIDE];
__device__ float g_redo[NCTAS * 256 * 64];
__device__ __forceinline__ uint8_t* tile_img(uint8_t* scr, int h, int isV, int blk) { return scr + h * HEAD_STRIDE + (size_t)(2 * blk + isV) * TILE_BYTES; }

#define TS(e)
#define ST2(k)

__device__ __forceinline__ uint32_t smem_u32(const void* p) { return (uint32_t)__cvta_generic_to_shared(p); }
__device__ __forceinline__ void wg_fence() { asm volatile("wgmma.fence.sync.aligned;\n" ::: "memory"); }
__device__ __forceinline__ void wg_commit() { asm volatile("wgmma.commit_group.sync.aligned;\n" ::: "memory"); }
template <int N> __device__ __forceinline__ void wg_wait() { asm volatile("wgmma.wait_group.sync.aligned %0;\n" ::"n"(N) : "memory"); }
template <int NR> __device__ __forceinline__ void fence_regs(float (&d)[NR]) {
#pragma unroll
  for (int i = 0; i < NR; i++) asm volatile("" : "+f"(d[i])::"memory");
}
template <int NR> __device__ __forceinline__ void fence_regs(uint32_t (&d)[NR]) {
#pragma unroll
  for (int i = 0; i < NR; i++) asm volatile("" : "+r"(d[i])::"memory");
}
__device__ __forceinline__ void bar_sync(int id, int n) { asm volatile("bar.sync %0, %1;\n" ::"r"(id), "r"(n) : "memory"); }
__device__ __forceinline__ void bar_arrive(int id, int n) { asm volatile("bar.arrive %0, %1;\n" ::"r"(id), "r"(n) : "memory"); }
__device__ __forceinline__ void bar_sync_sel(uint32_t second) {
  asm volatile("{\n.reg .pred p;\nsetp.ne.u32 p, %0, 0;\n@!p bar.sync 1, 256;\n@p bar.sync 2, 256;\n}\n" ::"r"(second) : "memory");
}
__device__ __forceinline__ void bar_arrive_sel(uint32_t second) {
  asm volatile("{\n.reg .pred p;\nsetp.ne.u32 p, %0, 0;\n@!p bar.arrive 1, 256;\n@p bar.arrive 2, 256;\n}\n" ::"r"(second) : "memory");
}
__device__ __forceinline__ void mbar_init(uint32_t bar, uint32_t count) {
  asm volatile("mbarrier.init.shared::cta.b64 [%0], %1;\n" ::"r"(bar), "r"(count) : "memory");
}
__device__ __forceinline__ void mbar_expect_tx(uint32_t bar, uint32_t bytes) {
  asm volatile("mbarrier.arrive.expect_tx.shared::cta.b64 _, [%0], %1;\n" ::"r"(bar), "r"(bytes) : "memory");
}
__device__ __forceinline__ void mbar_wait(uint32_t bar, uint32_t parity) {
  asm volatile(
      "{\n.reg .pred p;\n"
      "WAIT_LOOP:\n"
      "mbarrier.try_wait.parity.shared::cta.b64 p, [%0], %1;\n"
      "@p bra WAIT_DONE;\n"
      "bra WAIT_LOOP;\n"
      "WAIT_DONE:\n}\n" ::"r"(bar), "r"(parity) : "memory");
}
__device__ __forceinline__ uint32_t mbar_test(uint32_t bar, uint32_t parity) {
  uint32_t ok;
  asm volatile("{\n.reg .pred p;\nmbarrier.test_wait.parity.shared::cta.b64 p, [%1], %2;\nselp.u32 %0, 1, 0, p;\n}\n" : "=r"(ok) : "r"(bar), "r"(parity) : "memory");
  return ok;
}
__device__ __forceinline__ void mma_16816(float& c0, float& c1, float& c2, float& c3, uint32_t a0, uint32_t a1, uint32_t a2, uint32_t a3, uint32_t b0, uint32_t b1) {
  asm volatile("mma.sync.aligned.m16n8k16.row.col.f32.bf16.bf16.f32 {%0, %1, %2, %3}, {%4, %5, %6, %7}, {%8, %9}, {%0, %1, %2, %3};\n"
               : "+f"(c0), "+f"(c1), "+f"(c2), "+f"(c3) : "r"(a0), "r"(a1), "r"(a2), "r"(a3), "r"(b0), "r"(b1));
}
__device__ __forceinline__ float rcp_fast(float x) {
  float y;
  asm("rcp.approx.ftz.f32 %0, %1;\n" : "=f"(y) : "f"(x));
  return y;
}
__device__ __forceinline__ void mbar_arrive_local(uint32_t bar) {
  asm volatile("mbarrier.arrive.shared::cta.b64 _, [%0];\n" ::"r"(bar) : "memory");
}
__device__ __forceinline__ void mbar_arrive_cluster(uint32_t bar, uint32_t cta) {
  asm volatile(
      "{\n.reg .b32 ra;\n"
      "mapa.shared::cluster.u32 ra, %0, %1;\n"
      "mbarrier.arrive.shared::cluster.b64 _, [ra];\n}\n" ::"r"(bar), "r"(cta) : "memory");
}
__device__ __forceinline__ void bulk_load_mc(uint32_t dst, const void* src, uint32_t bytes, uint32_t bar, uint16_t mask) {
  asm volatile(
      "cp.async.bulk.shared::cluster.global.mbarrier::complete_tx::bytes.multicast::cluster [%0], [%1], %2, [%3], %4;\n" ::"r"(dst),
      "l"(src), "r"(bytes), "r"(bar), "h"(mask)
      : "memory");
}
__device__ __forceinline__ void bulk_load(uint32_t dst, const void* src, uint32_t bytes, uint32_t bar) {
  asm volatile("cp.async.bulk.shared::cluster.global.mbarrier::complete_tx::bytes [%0], [%1], %2, [%3];\n" ::"r"(dst), "l"(src),
               "r"(bytes), "r"(bar)
               : "memory");
}
__device__ __forceinline__ void tma_load_2d(uint32_t dst, const void* tmap, int c0, int c1, uint32_t bar) {
  asm volatile("cp.async.bulk.tensor.2d.shared::cluster.global.mbarrier::complete_tx::bytes [%0], [%1, {%3, %4}], [%2];\n" ::"r"(dst), "l"(tmap),
               "r"(bar), "r"(c0), "r"(c1)
               : "memory");
}
__device__ __forceinline__ void ldsm_x4(uint32_t& r0, uint32_t& r1, uint32_t& r2, uint32_t& r3, uint32_t addr) {
  asm volatile("ldmatrix.sync.aligned.m8n8.x4.shared.b16 {%0, %1, %2, %3}, [%4];\n" : "=r"(r0), "=r"(r1), "=r"(r2), "=r"(r3) : "r"(addr) : "memory");
}
__device__ __forceinline__ bool wg_any(bool p, int id) {
  uint32_t r;
  asm volatile("{\n.reg .pred p, q;\nsetp.ne.u32 p, %1, 0;\nbarrier.cta.red.or.aligned.pred q, %2, 128, p;\nselp.u32 %0, 1, 0, q;\n}\n"
               : "=r"(r) : "r"((uint32_t)p), "r"(id) : "memory");
  return r != 0;
}
__device__ __forceinline__ float ex2(float x) {
  float y;
  asm("ex2.approx.ftz.f32 %0, %1;\n" : "=f"(y) : "f"(x));
  return y;
}
__device__ __forceinline__ uint32_t pack_bf16(float lo, float hi) {
  uint32_t r;
  asm("cvt.rn.bf16x2.f32 %0, %1, %2;\n" : "=r"(r) : "f"(hi), "f"(lo));
  return r;
}
__device__ __forceinline__ uint64_t make_desc(uint32_t addr, uint32_t lbo, uint32_t sbo) {
  return (uint64_t)((addr & 0x3FFFF) >> 4) | ((uint64_t)(lbo >> 4) << 16) | ((uint64_t)(sbo >> 4) << 32) | (1ull << 62);
}

__device__ __forceinline__ void wgmma_rs_kmaj(float (&d)[64], uint32_t a0, uint32_t a1, uint32_t a2, uint32_t a3, uint64_t descB, int scaleD) {
  asm volatile("{\n.reg .pred p;\nsetp.ne.b32 p, %69, 0;\n"
    "wgmma.mma_async.sync.aligned.m64n128k16.f32.bf16.bf16 "
    "{%0, %1, %2, %3, %4, %5, %6, %7, %8, %9, %10, %11, %12, %13, %14, %15, "
    "%16, %17, %18, %19, %20, %21, %22, %23, %24, %25, %26, %27, %28, %29, %30, %31, "
    "%32, %33, %34, %35, %36, %37, %38, %39, %40, %41, %42, %43, %44, %45, %46, %47, "
    "%48, %49, %50, %51, %52, %53, %54, %55, %56, %57, %58, %59, %60, %61, %62, %63}, "
    "{%64, %65, %66, %67}, %68, p, 1, 1, 0;\n}\n"
    : "+f"(d[0]), "+f"(d[1]), "+f"(d[2]), "+f"(d[3]), "+f"(d[4]), "+f"(d[5]), "+f"(d[6]), "+f"(d[7]),
      "+f"(d[8]), "+f"(d[9]), "+f"(d[10]), "+f"(d[11]), "+f"(d[12]), "+f"(d[13]), "+f"(d[14]), "+f"(d[15]),
      "+f"(d[16]), "+f"(d[17]), "+f"(d[18]), "+f"(d[19]), "+f"(d[20]), "+f"(d[21]), "+f"(d[22]), "+f"(d[23]),
      "+f"(d[24]), "+f"(d[25]), "+f"(d[26]), "+f"(d[27]), "+f"(d[28]), "+f"(d[29]), "+f"(d[30]), "+f"(d[31]),
      "+f"(d[32]), "+f"(d[33]), "+f"(d[34]), "+f"(d[35]), "+f"(d[36]), "+f"(d[37]), "+f"(d[38]), "+f"(d[39]),
      "+f"(d[40]), "+f"(d[41]), "+f"(d[42]), "+f"(d[43]), "+f"(d[44]), "+f"(d[45]), "+f"(d[46]), "+f"(d[47]),
      "+f"(d[48]), "+f"(d[49]), "+f"(d[50]), "+f"(d[51]), "+f"(d[52]), "+f"(d[53]), "+f"(d[54]), "+f"(d[55]),
      "+f"(d[56]), "+f"(d[57]), "+f"(d[58]), "+f"(d[59]), "+f"(d[60]), "+f"(d[61]), "+f"(d[62]), "+f"(d[63])
    : "r"(a0), "r"(a1), "r"(a2), "r"(a3), "l"(descB), "r"(scaleD));
}

__device__ __forceinline__ void wgmma_ss_kmaj(float (&d)[64], uint64_t descA, uint64_t descB, int scaleD) {
  asm volatile("{\n.reg .pred p;\nsetp.ne.b32 p, %66, 0;\n"
    "wgmma.mma_async.sync.aligned.m64n128k16.f32.bf16.bf16 "
    "{%0, %1, %2, %3, %4, %5, %6, %7, %8, %9, %10, %11, %12, %13, %14, %15, "
    "%16, %17, %18, %19, %20, %21, %22, %23, %24, %25, %26, %27, %28, %29, %30, %31, "
    "%32, %33, %34, %35, %36, %37, %38, %39, %40, %41, %42, %43, %44, %45, %46, %47, "
    "%48, %49, %50, %51, %52, %53, %54, %55, %56, %57, %58, %59, %60, %61, %62, %63}, "
    "%64, %65, p, 1, 1, 0, 0;\n}\n"
    : "+f"(d[0]), "+f"(d[1]), "+f"(d[2]), "+f"(d[3]), "+f"(d[4]), "+f"(d[5]), "+f"(d[6]), "+f"(d[7]),
      "+f"(d[8]), "+f"(d[9]), "+f"(d[10]), "+f"(d[11]), "+f"(d[12]), "+f"(d[13]), "+f"(d[14]), "+f"(d[15]),
      "+f"(d[16]), "+f"(d[17]), "+f"(d[18]), "+f"(d[19]), "+f"(d[20]), "+f"(d[21]), "+f"(d[22]), "+f"(d[23]),
      "+f"(d[24]), "+f"(d[25]), "+f"(d[26]), "+f"(d[27]), "+f"(d[28]), "+f"(d[29]), "+f"(d[30]), "+f"(d[31]),
      "+f"(d[32]), "+f"(d[33]), "+f"(d[34]), "+f"(d[35]), "+f"(d[36]), "+f"(d[37]), "+f"(d[38]), "+f"(d[39]),
      "+f"(d[40]), "+f"(d[41]), "+f"(d[42]), "+f"(d[43]), "+f"(d[44]), "+f"(d[45]), "+f"(d[46]), "+f"(d[47]),
      "+f"(d[48]), "+f"(d[49]), "+f"(d[50]), "+f"(d[51]), "+f"(d[52]), "+f"(d[53]), "+f"(d[54]), "+f"(d[55]),
      "+f"(d[56]), "+f"(d[57]), "+f"(d[58]), "+f"(d[59]), "+f"(d[60]), "+f"(d[61]), "+f"(d[62]), "+f"(d[63])
    : "l"(descA), "l"(descB), "r"(scaleD));
}

__device__ __forceinline__ void wgmma_rs_nmaj(float (&d)[64], uint32_t a0, uint32_t a1, uint32_t a2, uint32_t a3, uint64_t descB, int scaleD) {
  asm volatile("{\n.reg .pred p;\nsetp.ne.b32 p, %69, 0;\n"
    "wgmma.mma_async.sync.aligned.m64n128k16.f32.bf16.bf16 "
    "{%0, %1, %2, %3, %4, %5, %6, %7, %8, %9, %10, %11, %12, %13, %14, %15, "
    "%16, %17, %18, %19, %20, %21, %22, %23, %24, %25, %26, %27, %28, %29, %30, %31, "
    "%32, %33, %34, %35, %36, %37, %38, %39, %40, %41, %42, %43, %44, %45, %46, %47, "
    "%48, %49, %50, %51, %52, %53, %54, %55, %56, %57, %58, %59, %60, %61, %62, %63}, "
    "{%64, %65, %66, %67}, %68, p, 1, 1, 1;\n}\n"
    : "+f"(d[0]), "+f"(d[1]), "+f"(d[2]), "+f"(d[3]), "+f"(d[4]), "+f"(d[5]), "+f"(d[6]), "+f"(d[7]),
      "+f"(d[8]), "+f"(d[9]), "+f"(d[10]), "+f"(d[11]), "+f"(d[12]), "+f"(d[13]), "+f"(d[14]), "+f"(d[15]),
      "+f"(d[16]), "+f"(d[17]), "+f"(d[18]), "+f"(d[19]), "+f"(d[20]), "+f"(d[21]), "+f"(d[22]), "+f"(d[23]),
      "+f"(d[24]), "+f"(d[25]), "+f"(d[26]), "+f"(d[27]), "+f"(d[28]), "+f"(d[29]), "+f"(d[30]), "+f"(d[31]),
      "+f"(d[32]), "+f"(d[33]), "+f"(d[34]), "+f"(d[35]), "+f"(d[36]), "+f"(d[37]), "+f"(d[38]), "+f"(d[39]),
      "+f"(d[40]), "+f"(d[41]), "+f"(d[42]), "+f"(d[43]), "+f"(d[44]), "+f"(d[45]), "+f"(d[46]), "+f"(d[47]),
      "+f"(d[48]), "+f"(d[49]), "+f"(d[50]), "+f"(d[51]), "+f"(d[52]), "+f"(d[53]), "+f"(d[54]), "+f"(d[55]),
      "+f"(d[56]), "+f"(d[57]), "+f"(d[58]), "+f"(d[59]), "+f"(d[60]), "+f"(d[61]), "+f"(d[62]), "+f"(d[63])
    : "r"(a0), "r"(a1), "r"(a2), "r"(a3), "l"(descB), "r"(scaleD));
}

struct DqCtx { const int* qk; const int* qv; const __nv_bfloat16 *ks, *kz, *vs, *vz; uint8_t* scr; };
__device__ __forceinline__ float bf_lo(uint32_t u) { return __uint_as_float(u << 16); }
__device__ __forceinline__ float bf_hi(uint32_t u) { return __uint_as_float(u & 0xffff0000u); }
__device__ __forceinline__ float bf_round(float x) { return __bfloat162float(__float2bfloat16_rn(x)); }
__device__ __forceinline__ uint32_t dq_pair_small(uint32_t a, uint32_t b, uint32_t z2, uint32_t ns2) {
  uint32_t r;
  asm("{\n.reg .b32 y, d;\n"
      "mul.rn.bf16x2 y, %1, %4;\n"
      "fma.rn.bf16x2 d, y, %5, %2;\n"
      "mul.rn.bf16x2 %0, d, %3;\n}\n" : "=r"(r) : "r"(a + (b << 16)), "r"(z2), "r"(ns2), "r"(0x7f007f00u), "r"(0xc280c280u));
  return r;
}
template <bool HI> __device__ __forceinline__ uint32_t dq_pair_small1(uint32_t a, uint32_t b, uint32_t z, uint32_t ns) {
  uint32_t r;
  if (HI)
    asm("{\n.reg .b32 y, d, zb, sb;\n.reg .b16 l, h;\n"
        "mov.b32 {l, h}, %2;\nmov.b32 zb, {h, h};\nmov.b32 {l, h}, %3;\nmov.b32 sb, {h, h};\n"
        "mul.rn.bf16x2 y, %1, %4;\n"
        "fma.rn.bf16x2 d, y, %5, zb;\n"
        "mul.rn.bf16x2 %0, d, sb;\n}\n" : "=r"(r) : "r"(a + (b << 16)), "r"(z), "r"(ns), "r"(0x7f007f00u), "r"(0xc280c280u));
  else
    asm("{\n.reg .b32 y, d, zb, sb;\n.reg .b16 l, h;\n"
        "mov.b32 {l, h}, %2;\nmov.b32 zb, {l, l};\nmov.b32 {l, h}, %3;\nmov.b32 sb, {l, l};\n"
        "mul.rn.bf16x2 y, %1, %4;\n"
        "fma.rn.bf16x2 d, y, %5, zb;\n"
        "mul.rn.bf16x2 %0, d, sb;\n}\n" : "=r"(r) : "r"(a + (b << 16)), "r"(z), "r"(ns), "r"(0x7f007f00u), "r"(0xc280c280u));
  return r;
}
__device__ __forceinline__ uint32_t dq_pair_any(int a, int b, uint32_t z2, uint32_t s2) {
  return pack_bf16(bf_round(bf_round((float)a) - bf_lo(z2)) * bf_lo(s2), bf_round(bf_round((float)b) - bf_hi(z2)) * bf_hi(s2));
}
struct DqLane {
  uint32_t srcK, srcV, dst;
  int rr0;
  __device__ __forceinline__ DqLane(int cta, int lane) {
    const int j = lane >> 1;
    rr0 = ((cta >> 2) & 7) * 16 + (cta & 3) * 2;
    srcK = (rr0 * DH + lane * 4) * 4;
    srcV = (rr0 * DH + 32 * (j >> 2) + 2 * (j & 3) + 16 * (lane & 1)) * 4;
    dst = (lane >> 4) * HALF_BYTES + rr0 * 128 + (((j ^ rr0) & 7) << 4) + (lane & 1) * 8;
  }
};
template <int OFF> __device__ __forceinline__ void st_v2(uint64_t addr, uint32_t a, uint32_t b) {
  asm volatile("st.global.v2.b32 [%0+%3], {%1, %2};\n" ::"l"(addr), "r"(a), "r"(b), "n"(OFF) : "memory");
}
__device__ __forceinline__ void dq_rows_any(const DqCtx& d, const DqLane& L, bool isV, int blk, int lane) {
  const int j = lane >> 1;
  const int c0 = isV ? 32 * (j >> 2) + 2 * (j & 3) + 16 * (lane & 1) : lane * 4, c1 = isV ? c0 + 8 : c0 + 2;
  const uint64_t dA = reinterpret_cast<uint64_t>(d.scr) + (uint32_t)((blk >> 4) * (uint32_t)HEAD_STRIDE + (2 * (blk & (NBLK - 1)) + isV) * TILE_BYTES + L.dst);
#pragma unroll 1
  for (int i = 0; i < 4; i++) {
    const int tok = blk * BN + L.rr0 + (i & 1) + (i >> 1) * 8;
    const int* src = (isV ? d.qv : d.qk) + (size_t)tok * DH;
    uint32_t za, zb, sa, sb;
    if (isV) {
      za = zb = (uint32_t)__bfloat16_as_ushort(d.vz[tok]) * 0x10001u; sa = sb = (uint32_t)__bfloat16_as_ushort(d.vs[tok]) * 0x10001u;
    } else {
      const uint32_t* zp = reinterpret_cast<const uint32_t*>(d.kz + blk * DH + lane * 4);
      const uint32_t* sp = reinterpret_cast<const uint32_t*>(d.ks + blk * DH + lane * 4);
      za = zp[0]; zb = zp[1]; sa = sp[0]; sb = sp[1];
    }
    st_v2<0>((dA ^ ((i & 1) * 0x90)) + (i >> 1) * 1024, dq_pair_any(src[c0], src[c0 + 1], za, sa), dq_pair_any(src[c1], src[c1 + 1], zb, sb));
  }
}
struct DqTask {
  uint32_t x[4][4];
  uint32_t z[2], s[2];
  template <bool isV> __device__ __forceinline__ void load(const DqCtx& d, const DqLane& L, int blk, int lane) {
    if (isV) {
      const uint8_t* src = reinterpret_cast<const uint8_t*>(d.qv) + (size_t)(uint32_t)(blk * (BN * DH * 4) + L.srcV);
#pragma unroll
      for (int i = 0; i < 4; i++) {
        const uint8_t* p = src + ((i & 1) + (i >> 1) * 8) * (DH * 4);
        const int2 a = __ldcs(reinterpret_cast<const int2*>(p)), b = __ldcs(reinterpret_cast<const int2*>(p + 32));
        x[i][0] = a.x; x[i][1] = a.y; x[i][2] = b.x; x[i][3] = b.y;
      }
      const uint32_t* zp = reinterpret_cast<const uint32_t*>(d.vz + blk * BN + L.rr0);
      const uint32_t* sp = reinterpret_cast<const uint32_t*>(d.vs + blk * BN + L.rr0);
      z[0] = __ldg(zp); z[1] = __ldg(zp + 4); s[0] = __ldg(sp); s[1] = __ldg(sp + 4);
    } else {
      const uint8_t* src = reinterpret_cast<const uint8_t*>(d.qk) + (size_t)(uint32_t)(blk * (BN * DH * 4) + L.srcK);
#pragma unroll
      for (int i = 0; i < 4; i++) {
        const int4 a = __ldcs(reinterpret_cast<const int4*>(src + ((i & 1) + (i >> 1) * 8) * (DH * 4)));
        x[i][0] = a.x; x[i][1] = a.y; x[i][2] = a.z; x[i][3] = a.w;
      }
      const uint32_t o = blk * (DH * 2) + lane * 8;
      const uint2 zz = __ldg(reinterpret_cast<const uint2*>(reinterpret_cast<const uint8_t*>(d.kz) + o));
      const uint2 ss = __ldg(reinterpret_cast<const uint2*>(reinterpret_cast<const uint8_t*>(d.ks) + o));
      z[0] = zz.x; z[1] = zz.y; s[0] = ss.x; s[1] = ss.y;
    }
  }
  template <bool isV> __device__ __forceinline__ bool store(const DqCtx& d, const DqLane& L, int blk) const {
    uint32_t any = 0;
#pragma unroll
    for (int i = 0; i < 4; i++) any |= x[i][0] | x[i][1] | x[i][2] | x[i][3];
    if (__builtin_expect(__any_sync(0xffffffffu, any >= 256u), 0)) return true;
    const uint64_t dA = reinterpret_cast<uint64_t>(d.scr) + (uint32_t)((blk >> 4) * (uint32_t)HEAD_STRIDE + (2 * (blk & (NBLK - 1)) + isV) * TILE_BYTES + L.dst);
    const uint64_t dB = dA ^ 0x90;
    const uint32_t ns0 = s[0] ^ 0x80008000u, ns1 = s[1] ^ 0x80008000u;
    if (isV) {
      st_v2<0>(dA, dq_pair_small1<false>(x[0][0], x[0][1], z[0], ns0), dq_pair_small1<false>(x[0][2], x[0][3], z[0], ns0));
      st_v2<0>(dB, dq_pair_small1<true>(x[1][0], x[1][1], z[0], ns0), dq_pair_small1<true>(x[1][2], x[1][3], z[0], ns0));
      st_v2<1024>(dA, dq_pair_small1<false>(x[2][0], x[2][1], z[1], ns1), dq_pair_small1<false>(x[2][2], x[2][3], z[1], ns1));
      st_v2<1024>(dB, dq_pair_small1<true>(x[3][0], x[3][1], z[1], ns1), dq_pair_small1<true>(x[3][2], x[3][3], z[1], ns1));
    } else {
      st_v2<0>(dA, dq_pair_small(x[0][0], x[0][1], z[0], ns0), dq_pair_small(x[0][2], x[0][3], z[1], ns1));
      st_v2<0>(dB, dq_pair_small(x[1][0], x[1][1], z[0], ns0), dq_pair_small(x[1][2], x[1][3], z[1], ns1));
      st_v2<1024>(dA, dq_pair_small(x[2][0], x[2][1], z[0], ns0), dq_pair_small(x[2][2], x[2][3], z[1], ns1));
      st_v2<1024>(dB, dq_pair_small(x[3][0], x[3][1], z[0], ns0), dq_pair_small(x[3][2], x[3][3], z[1], ns1));
    }
    return false;
  }
};
__device__ __forceinline__ unsigned* tile_cnt(uint8_t* scr, int h, int t) { return reinterpret_cast<unsigned*>(scr + h * HEAD_STRIDE + CNT_OFF) + t * 32; }
__device__ __forceinline__ void dq_publish(unsigned* cnt, int lane) {
  asm volatile("fence.proxy.async.global;\n" ::: "memory");
  __syncwarp();
  if (lane == 0) asm volatile("red.release.gpu.global.add.u32 [%0], 1;\n" ::"l"(cnt) : "memory");
}

__global__ void __launch_bounds__(256) dequant_kernel(const int* __restrict__ qk, const int* __restrict__ qv,
                                                      const __nv_bfloat16* __restrict__ ks, const __nv_bfloat16* __restrict__ kz,
                                                      const __nv_bfloat16* __restrict__ vs, const __nv_bfloat16* __restrict__ vz, uint8_t* scr) {
  constexpr int ROWS_PER_WARP = 4;
  const int lane = threadIdx.x & 31;
  const int warp = blockIdx.x * 8 + (threadIdx.x >> 5);
  const int row0 = warp * ROWS_PER_WARP;
  const bool isV = row0 >= HKV * SKV;
  const int r0 = isV ? row0 - HKV * SKV : row0;
  const int* src = (isV ? qv : qk) + (size_t)r0 * DH + lane * 4;
  int4 x[ROWS_PER_WARP];
#pragma unroll
  for (int i = 0; i < ROWS_PER_WARP; i++) x[i] = __ldcs(reinterpret_cast<const int4*>(src + i * DH));
  float z[4], s[4];
  if (!isV) {
    const int g = r0 / BN;
    const uint2 zz = *reinterpret_cast<const uint2*>(kz + (size_t)g * DH + lane * 4);
    const uint2 ss = *reinterpret_cast<const uint2*>(ks + (size_t)g * DH + lane * 4);
    z[0] = __uint_as_float(zz.x << 16); z[1] = __uint_as_float(zz.x & 0xffff0000u);
    z[2] = __uint_as_float(zz.y << 16); z[3] = __uint_as_float(zz.y & 0xffff0000u);
    s[0] = __uint_as_float(ss.x << 16); s[1] = __uint_as_float(ss.x & 0xffff0000u);
    s[2] = __uint_as_float(ss.y << 16); s[3] = __uint_as_float(ss.y & 0xffff0000u);
  }
  uint8_t* img = tile_img(scr, r0 / SKV, isV, (r0 / BN) & (NBLK - 1));
  const int J = lane >> 3, c = (lane & 7) >> 1, sb = lane & 1;
  const int j = 4 * J + 2 * sb + (c & 1);
  const int half = j >> 3, ch = j & 7;
#pragma unroll
  for (int i = 0; i < ROWS_PER_WARP; i++) {
    const int r = r0 + i;
    if (isV) {
      const float zv = __bfloat162float(vz[r]), sv = __bfloat162float(vs[r]);
#pragma unroll
      for (int e = 0; e < 4; e++) { z[e] = zv; s[e] = sv; }
    }
    const int xi[4] = {x[i].x, x[i].y, x[i].z, x[i].w};
    float o[4];
#pragma unroll
    for (int e = 0; e < 4; e++) {
      const float qf = __bfloat162float(__float2bfloat16_rn((float)xi[e]));
      const float df = __bfloat162float(__float2bfloat16_rn(qf - z[e]));
      o[e] = df * s[e];
    }
    const uint32_t p0 = pack_bf16(o[0], o[1]), p1 = pack_bf16(o[2], o[3]);
    const int rr = r & (BN - 1);
    uint2 w;
    if (isV) {
      const uint32_t send = (c & 1) ? p0 : p1;
      const uint32_t recv = __shfl_xor_sync(0xffffffffu, send, 2);
      if (c & 1) { w.x = recv; w.y = p1; } else { w.x = p0; w.y = recv; }
      *reinterpret_cast<uint2*>(img + half * HALF_BYTES + rr * 128 + ((ch ^ (rr & 7)) << 4) + (c >> 1) * 8) = w;
    } else {
      w.x = p0; w.y = p1;
      *reinterpret_cast<uint2*>(img + (lane >> 4) * HALF_BYTES + rr * 128 + ((((lane >> 1) & 7) ^ (rr & 7)) << 4) + (lane & 1) * 8) = w;
    }
  }
}

constexpr float SCALE_LOG2 = 0.08838834764831845f * 1.4426950408889634f;
#define SPLIT 5
#define DEPD 2
constexpr float SUM_THR = 4294967296.0f;

__device__ __forceinline__ void issue_qk(float (&S)[64], const uint32_t (&Q)[32], uint32_t kaddr) {
  const uint64_t d0 = make_desc(kaddr, 16, 1024);
#pragma unroll
  for (int k = 0; k < 8; k++)
    wgmma_rs_kmaj(S, Q[4 * k], Q[4 * k + 1], Q[4 * k + 2], Q[4 * k + 3], d0 + (uint64_t)(((k & 3) * 32 + (k >> 2) * HALF_BYTES) >> 4), k != 0);
}
__device__ __forceinline__ void issue_qk_ss(float (&S)[64], uint32_t qaddr, uint32_t kaddr) {
  const uint64_t a0 = make_desc(qaddr, 16, 1024), d0 = make_desc(kaddr, 16, 1024);
#pragma unroll
  for (int k = 0; k < 8; k++) {
    const uint64_t off = (uint64_t)(((k & 3) * 32 + (k >> 2) * HALF_BYTES) >> 4);
    wgmma_ss_kmaj(S, a0 + off, d0 + off, k != 0);
  }
}
__device__ __forceinline__ void issue_pv(float (&O)[64], const uint32_t (&P)[32], uint32_t vaddr, int acc) {
  const uint64_t d0 = make_desc(vaddr, HALF_BYTES, 1024);
#pragma unroll
  for (int k = 0; k < 8; k++)
    wgmma_rs_nmaj(O, P[4 * k], P[4 * k + 1], P[4 * k + 2], P[4 * k + 3], d0 + (uint64_t)((k * 2048) >> 4), (k != 0) | acc);
}
__device__ __forceinline__ float tie(float a, float b, uint32_t z) {
  uint32_t r;
  asm("lop3.b32 %0, %1, %2, %3, 0xF8;\n" : "=r"(r) : "r"(__float_as_uint(a)), "r"(__float_as_uint(b)), "r"(z));
  return __uint_as_float(r);
}

__device__ __forceinline__ uint32_t tieu(uint32_t a, float b, uint32_t z) {
  uint32_t r;
  asm("lop3.b32 %0, %1, %2, %3, 0xF8;\n" : "=r"(r) : "r"(a), "r"(__float_as_uint(b)), "r"(z));
  return r;
}

#define BAR_SYNC_MINE bar_sync(my_bar, 256)
#define BAR_ARRIVE_OTHER bar_arrive(other_bar, 256)
#define LDSM_POS 0
template <bool B> struct BoolC { static constexpr bool value = B; };

#define QMODE 0
#define EARLY_NEXT
#define Q_DELAY 300
#define Q_DELAY1 Q_DELAY
#define NPRE 1
#define POLLW 4
#define PDEPTH 1
__global__ void __cluster_dims__(CL, 1, 1) __launch_bounds__(384, 1)
attn_kernel(const DqCtx dq, const __nv_bfloat16* __restrict__ q, __nv_bfloat16* __restrict__ out, const uint32_t zero, const int fused,
            const __grid_constant__ CUtensorMap tmq) {
  extern __shared__ uint8_t smem_raw[];
  const uint32_t sbase = (smem_u32(smem_raw) + 1023u) & ~1023u;
  const uint32_t sK = sbase, sV = sbase + NK * TILE_BYTES, sQ = sbase + (NK + NV) * TILE_BYTES;
  const uint32_t bars = sbase + (NK + NV + 1) * TILE_BYTES;
  const uint32_t fullK = bars, fullV = bars + 8 * NK, emptyK = bars + 8 * (NK + NV), emptyV = emptyK + 8 * NK;
  const uint32_t fullQ = emptyV + 8 * NV, emptyQ = fullQ + 8;

  const int cta = blockIdx.x;
  const int warp = __shfl_sync(0xffffffffu, (int)(threadIdx.x >> 5), 0);
  const int lane = threadIdx.x & 31;
  const int wg = warp >> 2;
  const uint32_t rank = cta & (CL - 1);
  const int h = cta >> 5;
  const int row0 = cta * (TILES_PER_CTA * 128);
  constexpr int TOTAL = TILES_PER_CTA * NBLK;

  const DqLane L(cta, lane);
  DqTask task;
  uint32_t todo = 0;
  if (warp >= 4) {
    uint4 q0[8];
    asm volatile("barrier.cluster.arrive.relaxed.aligned;\n" ::: "memory");
    if (Q_DELAY + Q_DELAY1 > 0) { const uint32_t t0 = clock(); while ((uint32_t)clock() - t0 < (warp >= 8 ? Q_DELAY1 : Q_DELAY)) { } }
    const __nv_bfloat16* qs = q + (size_t)(row0 + (warp - 4) * 16 + (lane >> 4)) * DH + (lane & 15) * 8;
#pragma unroll
    for (int i = 0; i < 8; i++) {
      q0[i] = __ldcs(reinterpret_cast<const uint4*>(qs + 2 * i * DH));
    }
#pragma unroll
    for (int i = 0; i < 8; i++) {
      const int rr = (warp - 4) * 16 + 2 * i + (lane >> 4);
      asm volatile("st.shared.v4.b32 [%0], {%1, %2, %3, %4};\n" ::"r"(sQ + ((lane >> 3) & 1) * HALF_BYTES + rr * 128 + (((lane ^ rr) & 7) << 4)),
                   "r"(q0[i].x), "r"(q0[i].y), "r"(q0[i].z), "r"(q0[i].w) : "memory");
    }
    asm volatile("fence.proxy.async.shared::cta;\n" ::: "memory");
  } else if (warp == 3) {
    ST2(0);
    if (lane == 0) {
      for (int s = 0; s < NK; s++) { mbar_init(fullK + 8 * s, 1); mbar_init(emptyK + 8 * s, 8 * CL); }
      for (int s = 0; s < NV; s++) { mbar_init(fullV + 8 * s, 1); mbar_init(emptyV + 8 * s, 8 * CL); }
      mbar_init(fullQ, 1); mbar_init(emptyQ, 8);
      asm volatile("fence.mbarrier_init.release.cluster;\n" ::: "memory");
    }
    __syncwarp();
    asm volatile("barrier.cluster.arrive.relaxed.aligned;\n" ::: "memory");
    ST2(1);
  } else {
    asm volatile("barrier.cluster.arrive.relaxed.aligned;\n" ::: "memory");
    if (fused) {
      if (warp < 2) task.load<false>(dq, L, h * NBLK + warp, lane); else task.load<true>(dq, L, h * NBLK, lane);
      const int t0 = warp < 2 ? 2 * warp : 1;
      if (warp < 2 ? task.store<false>(dq, L, h * NBLK + warp) : task.store<true>(dq, L, h * NBLK)) todo = 1u << t0;
      task.load<true>(dq, L, h * NBLK + 1 + warp, lane);
      asm volatile("fence.proxy.async.global;\n" ::: "memory");
      __syncwarp();
      if (lane == 0 && !todo) asm volatile("red.release.gpu.global.add.u32 [%0], 1;\n" ::"l"(tile_cnt(dq.scr, h, t0)) : "memory");
    }
  }
  asm volatile("barrier.cluster.wait.aligned;\n" ::: "memory");

  if (wg == 0) {
    if (warp == 3) ST2(2);
    asm volatile("setmaxnreg.dec.sync.aligned.u32 40;\n");
    if (warp == 3) {
      ST2(3);
      const uint8_t* img = dq.scr + h * HEAD_STRIDE + rank * SLICE;
      const unsigned* cnt = tile_cnt(dq.scr, h, lane);
      uint32_t ready = fused ? 0u : ~0u;
      auto need = [&](int t) {
        if ((ready >> t) & 1) return;
        unsigned n = 0;
        do {
          unsigned v = 0;
          if ((unsigned)(lane - (t - 1)) < POLLW) asm volatile("ld.acquire.gpu.global.u32 %0, [%1];\n" : "=r"(v) : "l"(cnt) : "memory");
          ready |= __ballot_sync(0xffffffffu, v >= SLICES);
          if (++n > (1u << 24)) __trap();
        } while (!((ready >> t) & 1));
        __syncwarp();
        asm volatile("fence.proxy.async.global;\n" ::: "memory");
      };
      int ks = 0, kph = 1, vs = 0, vph = 1;
      for (int i = 0; i <= TOTAL; i++) {
        if (i < TOTAL) {
          mbar_wait(emptyK + 8 * ks, kph);
          if (i < NBLK) need(2 * i);
          if (lane == 0) {
            mbar_expect_tx(fullK + 8 * ks, TILE_BYTES);
            bulk_load_mc(sK + ks * TILE_BYTES + rank * SLICE, img + (size_t)(i & (NBLK - 1)) * (2 * TILE_BYTES), SLICE, fullK + 8 * ks, (uint16_t)((1 << CL) - 1));
          }
          if (i < 2) ST2(4 + 2 * i);
          if (++ks == NK) { ks = 0; kph ^= 1; }
        }
        if (i > 0) {
          mbar_wait(emptyV + 8 * vs, vph);
          if (i <= NBLK) need(2 * i - 1);
          if (i == 1) ST2(7);
          if (lane == 0) {
            mbar_expect_tx(fullV + 8 * vs, TILE_BYTES);
            bulk_load_mc(sV + vs * TILE_BYTES + rank * SLICE, img + (size_t)((i - 1) & (NBLK - 1)) * (2 * TILE_BYTES) + TILE_BYTES, SLICE, fullV + 8 * vs, (uint16_t)((1 << CL) - 1));
          }
          if (i == 1) ST2(8);
          if (++vs == NV) { vs = 0; vph ^= 1; }
        }
        const int p = (i & (NBLK - 1)) - QFIRST;
        if (p >= 0 && p < QP && i < TOTAL - NBLK) {
          if (p == 0) {
            mbar_wait(emptyQ, ((i >> 4) & 1));
            if (lane == 0) mbar_expect_tx(fullQ, TILE_BYTES);
          }
          if (lane == 0) tma_load_2d(sQ + (p & 1) * HALF_BYTES + (p >> 1) * (QROWS * 128), &tmq, (p & 1) * 64, row0 + ((i >> 4) + 1) * 128 + (p >> 1) * QROWS, fullQ);
        }
      }
      if (fused) {
        unsigned* done = reinterpret_cast<unsigned*>(dq.scr + CNT_OFF) + 2 * NBLK * 32;
        unsigned last = 0;
        if (lane == 0) last = atomicAdd(done, 1u) == NCTAS - 1;
        if (__shfl_sync(0xffffffffu, last, 0)) {
#pragma unroll
          for (int k = 0; k < HKV; k++) *tile_cnt(dq.scr, k, lane) = 0;
          if (lane == 0) *done = 0;
        }
      }
    } else if (fused) {
#pragma unroll 1
      for (int b = 2 + warp; b <= NBLK; b += 3) {
        if (task.store<true>(dq, L, h * NBLK + b - 1)) todo |= 1u << (2 * b - 1);
        if (b < NBLK) {
          task.load<false>(dq, L, h * NBLK + b, lane);
          if (task.store<false>(dq, L, h * NBLK + b)) todo |= 1u << (2 * b);
        }
        if (b + 3 <= NBLK) task.load<true>(dq, L, h * NBLK + b + 2, lane);
        asm volatile("fence.proxy.async.global;\n" ::: "memory");
        __syncwarp();
        if (lane < (b < NBLK ? 2 : 1) && !((todo >> (2 * b - 1 + lane)) & 1)) asm volatile("red.release.gpu.global.add.u32 [%0], 1;\n" ::"l"(tile_cnt(dq.scr, h, 2 * b - 1 + lane)) : "memory");
      }
#pragma unroll 1
      while (__builtin_expect(todo != 0, 0)) {
        const int t = __ffs(todo) - 1;
        todo &= todo - 1;
        dq_rows_any(dq, L, t & 1, h * NBLK + (t >> 1), lane);
        dq_publish(tile_cnt(dq.scr, h, t), lane);
      }
    }
  } else {
    asm volatile("setmaxnreg.inc.sync.aligned.u32 232;\n");
    uint32_t tid;
    asm volatile("mov.u32 %0, %%tid.x;\n" : "=r"(tid));
    const int my_bar = tid >> 7, other_bar = 3 - my_bar;
    const int cw = my_bar - 1;
    const int wq = (tid >> 5) & 3;
    const int c = lane & 3;
    const int myrow = row0 + cw * 64 + wq * 16 + (lane >> 2);
    __nv_bfloat16* optr = out + (size_t)myrow * DH + 8 * c;
    const uint32_t qaddr = sQ + (cw * 64 + wq * 16 + (lane & 15)) * 128 + ((((lane >> 4) ^ lane) & 7) << 4);

    float S[64], O[64];
    uint32_t P[32], Q[32];
    float m0, m1, l0 = 0.f, l1 = 0.f;
    float s0, s1;
#pragma unroll
    for (int i = 0; i < 64; i++) { S[i] = 0.f; O[i] = 0.f; }

    auto ldsm_q = [&]() {
#pragma unroll
      for (int k = 0; k < 8; k++) ldsm_x4(Q[4 * k], Q[4 * k + 1], Q[4 * k + 2], Q[4 * k + 3], (qaddr ^ ((k & 3) << 5)) + (k >> 2) * HALF_BYTES);
    };
    auto release = [&](uint32_t bar) {
      if (lane < CL) mbar_arrive_cluster(bar, lane);
    };
    auto exps = [&](int k0, int k1, float b0, float b1, float (&hist)[8][2]) {
#pragma unroll
      for (int k = 0; k < 8; k++) {
        if (k >= k0 && k < k1) {
          float c0 = b0, c1 = b1;
          if (k - DEPD >= 0) { c0 = tie(b0, hist[k - DEPD][0], zero); c1 = tie(b1, hist[k - DEPD][1], zero); }
          float a0 = k ? hist[k - 1][0] : 0.f, a1 = k ? hist[k - 1][1] : 0.f;
#pragma unroll
          for (int j = 2 * k; j < 2 * k + 2; j++) {
            S[4 * j + 0] = ex2(fmaf(S[4 * j + 0], SCALE_LOG2, c0));
            S[4 * j + 1] = ex2(fmaf(S[4 * j + 1], SCALE_LOG2, c0));
            S[4 * j + 2] = ex2(fmaf(S[4 * j + 2], SCALE_LOG2, c1));
            S[4 * j + 3] = ex2(fmaf(S[4 * j + 3], SCALE_LOG2, c1));
            if (j == 0) { a0 = S[0] + S[1]; a1 = S[2] + S[3]; }
            else { a0 += S[4 * j + 0]; a0 += S[4 * j + 1]; a1 += S[4 * j + 2]; a1 += S[4 * j + 3]; }
          }
          hist[k][0] = a0; hist[k][1] = a1;
        }
      }
    };
    auto convert_p = [&]() {
#pragma unroll
      for (int i = 0; i < 32; i++) P[i] = pack_bf16(S[2 * i], S[2 * i + 1]);
    };
    auto redo_block = [&](uint32_t kaddr, int tile) {
      const uint32_t* qp = reinterpret_cast<const uint32_t*>(q + ((size_t)myrow + tile * 128) * DH) + c;
#pragma unroll
      for (int k = 0; k < 8; k++) {
        P[4 * k] = qp[8 * k]; P[4 * k + 1] = qp[8 * k + 4 * DH]; P[4 * k + 2] = qp[8 * k + 4]; P[4 * k + 3] = qp[8 * k + 4 + 4 * DH];
      }
      const uint32_t a0 = kaddr + (lane & 7) * 128 + ((((lane >> 3) ^ lane) & 7) << 4);
      float* T = g_redo + (cta * 256 + (int)tid - 128);
      constexpr int TS_ = NCTAS * 256;
      float x0 = m0, x1 = m1;
#pragma unroll 1
      for (int j = 0; j < 16; j++) {
        float c0 = 0.f, c1 = 0.f, c2 = 0.f, c3 = 0.f;
#pragma unroll
        for (int kq = 0; kq < 4; kq++) {
          uint32_t b0, b1, b2, b3;
          ldsm_x4(b0, b1, b2, b3, ((a0 ^ ((kq & 1) << 6)) + (kq >> 1) * HALF_BYTES + j * 1024));
          mma_16816(c0, c1, c2, c3, P[8 * kq], P[8 * kq + 1], P[8 * kq + 2], P[8 * kq + 3], b0, b1);
          mma_16816(c0, c1, c2, c3, P[8 * kq + 4], P[8 * kq + 5], P[8 * kq + 6], P[8 * kq + 7], b2, b3);
        }
        T[(4 * j) * TS_] = c0; T[(4 * j + 1) * TS_] = c1; T[(4 * j + 2) * TS_] = c2; T[(4 * j + 3) * TS_] = c3;
        x0 = fmaxf(x0, fmaxf(c0, c1)); x1 = fmaxf(x1, fmaxf(c2, c3));
      }
      x0 = fmaxf(x0, __shfl_xor_sync(0xffffffffu, x0, 1)); x1 = fmaxf(x1, __shfl_xor_sync(0xffffffffu, x1, 1));
      x0 = fmaxf(x0, __shfl_xor_sync(0xffffffffu, x0, 2)); x1 = fmaxf(x1, __shfl_xor_sync(0xffffffffu, x1, 2));
      const float a0f = ex2((m0 - x0) * SCALE_LOG2), a1f = ex2((m1 - x1) * SCALE_LOG2);
      m0 = x0; m1 = x1; l0 *= a0f; l1 *= a1f;
#pragma unroll
      for (int j = 0; j < 16; j++) { O[4 * j] *= a0f; O[4 * j + 1] *= a0f; O[4 * j + 2] *= a1f; O[4 * j + 3] *= a1f; }
      const float b0 = -m0 * SCALE_LOG2, b1 = -m1 * SCALE_LOG2;
      s0 = 0.f; s1 = 0.f;
#pragma unroll 1
      for (int j = 0; j < 16; j++) {
        const float e0 = ex2(fmaf(T[(4 * j) * TS_], SCALE_LOG2, b0)), e1 = ex2(fmaf(T[(4 * j + 1) * TS_], SCALE_LOG2, b0));
        const float e2 = ex2(fmaf(T[(4 * j + 2) * TS_], SCALE_LOG2, b1)), e3 = ex2(fmaf(T[(4 * j + 3) * TS_], SCALE_LOG2, b1));
        s0 += e0 + e1; s1 += e2 + e3;
        T[(4 * j) * TS_] = __uint_as_float(pack_bf16(e0, e1)); T[(4 * j + 1) * TS_] = __uint_as_float(pack_bf16(e2, e3));
      }
#pragma unroll
      for (int j = 0; j < 16; j++) { P[2 * j] = __float_as_uint(T[(4 * j) * TS_]); P[2 * j + 1] = __float_as_uint(T[(4 * j + 1) * TS_]); }
    };
    auto pack_o = [&](float r0, float r1) {
#pragma unroll
      for (int J = 0; J < 4; J++) {
        float* o = &O[16 * J];
        asm volatile("{\n.reg .f32 t<16>;\n.reg .b32 u<8>;\n"
            "mul.f32 t0, %0, %16;\nmul.f32 t1, %1, %16;\nmul.f32 t2, %2, %17;\nmul.f32 t3, %3, %17;\n"
            "mul.f32 t4, %4, %16;\nmul.f32 t5, %5, %16;\nmul.f32 t6, %6, %17;\nmul.f32 t7, %7, %17;\n"
            "mul.f32 t8, %8, %16;\nmul.f32 t9, %9, %16;\nmul.f32 t10, %10, %17;\nmul.f32 t11, %11, %17;\n"
            "mul.f32 t12, %12, %16;\nmul.f32 t13, %13, %16;\nmul.f32 t14, %14, %17;\nmul.f32 t15, %15, %17;\n"
            "cvt.rn.bf16x2.f32 u0, t1, t0;\ncvt.rn.bf16x2.f32 u1, t5, t4;\ncvt.rn.bf16x2.f32 u2, t9, t8;\ncvt.rn.bf16x2.f32 u3, t13, t12;\n"
            "cvt.rn.bf16x2.f32 u4, t3, t2;\ncvt.rn.bf16x2.f32 u5, t7, t6;\ncvt.rn.bf16x2.f32 u6, t11, t10;\ncvt.rn.bf16x2.f32 u7, t15, t14;\n"
            "mov.b32 %0, u0;\nmov.b32 %1, u1;\nmov.b32 %2, u2;\nmov.b32 %3, u3;\n"
            "mov.b32 %4, u4;\nmov.b32 %5, u5;\nmov.b32 %6, u6;\nmov.b32 %7, u7;\n}\n"
            : "+f"(o[0]), "+f"(o[1]), "+f"(o[2]), "+f"(o[3]), "+f"(o[4]), "+f"(o[5]), "+f"(o[6]), "+f"(o[7]),
              "+f"(o[8]), "+f"(o[9]), "+f"(o[10]), "+f"(o[11]), "+f"(o[12]), "+f"(o[13]), "+f"(o[14]), "+f"(o[15])
            : "f"(r0), "f"(r1));
      }
    };
    auto store_o = [&](int tile) {
      __nv_bfloat16* o = optr + (size_t)tile * 128 * DH;
#pragma unroll
      for (int J = 0; J < 4; J++) {
        asm volatile("st.global.v4.b32 [%0], {%1, %2, %3, %4};\n" :: "l"(o + 32 * J), "f"(O[16 * J]), "f"(O[16 * J + 1]), "f"(O[16 * J + 2]), "f"(O[16 * J + 3]) : "memory");
        asm volatile("st.global.v4.b32 [%0], {%1, %2, %3, %4};\n" :: "l"(o + 8 * DH + 32 * J), "f"(O[16 * J + 4]), "f"(O[16 * J + 5]), "f"(O[16 * J + 6]), "f"(O[16 * J + 7]) : "memory");
      }
    };
#define EPI_MODE 1
#define STORE_AT_SETTLE store_o((i >> 4) - 1)
    auto settle = [&](int i, uint32_t kprev) {
      const int blk = i & (NBLK - 1);
      if (blk == 0) {
        if (i > 0) STORE_AT_SETTLE;
        l0 = 0.f; l1 = 0.f;
      }
      if (__any_sync(0xffffffffu, !(s0 <= SUM_THR) || !(s1 <= SUM_THR))) redo_block(kprev, i >> 4);
      l0 += s0; l1 += s1;
      if (blk == NBLK - 1) {
        l0 += __shfl_xor_sync(0xffffffffu, l0, 1); l1 += __shfl_xor_sync(0xffffffffu, l1, 1);
        l0 += __shfl_xor_sync(0xffffffffu, l0, 2); l1 += __shfl_xor_sync(0xffffffffu, l1, 2);
        l0 = rcp_fast(l0); l1 = rcp_fast(l1);
      }
    };

    int ks = 0, kph = 0, vs = 0, vph = 0;
    uint32_t kprev = sK, relKprev = emptyK;
    if (cw == 1) bar_arrive(1, 256);
    __syncwarp();
    ldsm_q();

    {
      if (warp == 4) ST2(9);
      mbar_wait(fullK, 0);
      if (warp == 4) ST2(10);
      BAR_SYNC_MINE;
      fence_regs(Q); fence_regs(S);
      wg_fence();
      issue_qk(S, Q, sK);
      wg_commit();
      BAR_ARRIVE_OTHER;
      if (lane == 0) mbar_arrive_local(emptyQ);
      ks = 1;
      if (warp == 4) ST2(11);
      wg_wait<0>();
      fence_regs(S);
      if (warp == 4) ST2(12);
      m0 = __shfl_sync(0xffffffffu, S[0], lane & ~3); m1 = __shfl_sync(0xffffffffu, S[2], lane & ~3);
      float hist[8][2];
      exps(0, 8, -m0 * SCALE_LOG2, -m1 * SCALE_LOG2, hist);
      convert_p();
      s0 = hist[7][0]; s1 = hist[7][1];
      if (warp == 4) ST2(13);
      mbar_wait(fullK + 8 * ks, kph);
      if (warp == 4) ST2(14);
      mbar_wait(fullV + 8 * vs, vph);
      if (warp == 4) ST2(15);
    }
    auto iteration = [&](auto pre_c, int i) {
      constexpr bool PRE = decltype(pre_c)::value;
      const int blk = PRE ? NBLK - 2 : (i & (NBLK - 1));
      const uint32_t kaddr = sK + ks * TILE_BYTES, vaddr = sV + vs * TILE_BYTES;
      const uint32_t relK = emptyK + 8 * ks, relV = emptyV + 8 * vs;
      if (++ks == NK) { ks = 0; kph ^= 1; }
      if (++vs == NV) { vs = 0; vph ^= 1; }
      const uint32_t nextK = fullK + 8 * ks, nextV = fullV + 8 * vs;
      BAR_SYNC_MINE;
      fence_regs(Q); fence_regs(S);
      wg_fence();
      issue_qk(S, Q, kaddr);
      wg_commit();
      settle(i, kprev);
      release(relKprev);
      kprev = kaddr; relKprev = relK;
      fence_regs(P); fence_regs(O);
      wg_fence();
      issue_pv(O, P, vaddr, blk != 0);
      wg_commit();
      BAR_ARRIVE_OTHER;
      if (PRE) mbar_wait(fullQ, (((i + 2) >> 4) & 1) ^ 1);
      else if (blk == NBLK - 1 && lane == 0) mbar_arrive_local(emptyQ);
      wg_wait<1>();
      fence_regs(S); fence_regs(Q);
      if (PRE) { if (LDSM_POS == 0) ldsm_q(); }
      else if (blk == NBLK - 1) { m0 = __shfl_sync(0xffffffffu, S[0], lane & ~3); m1 = __shfl_sync(0xffffffffu, S[2], lane & ~3); }
      const float b0 = -m0 * SCALE_LOG2, b1 = -m1 * SCALE_LOG2;
      float hist[8][2];
      exps(0, 8, b0, b1, hist);
      const uint32_t tK = mbar_test(nextK, tieu(kph, hist[SPLIT - 1][0], zero));
      const uint32_t tV = mbar_test(nextV, tieu(vph, hist[SPLIT - 1][1], zero));
      wg_wait<0>();
      const bool okK = __all_sync(0xffffffffu, tK) || (i + 2 >= TOTAL);
      const bool okV = __all_sync(0xffffffffu, tV);
      fence_regs(O); fence_regs(P);
      release(relV);
      convert_p();
      s0 = hist[7][0]; s1 = hist[7][1];
      if (PRE && LDSM_POS == 1) ldsm_q();
      if (!PRE && blk == NBLK - 1) {
        pack_o(l0, l1);
      }
      if (!okK) mbar_wait(nextK, kph);
      if (!okV) mbar_wait(nextV, vph);
    };
#pragma unroll 1
    for (int i = 0; i < TOTAL - 1; i++) {
      if ((i & (NBLK - 1)) == NBLK - 2 && i + 2 < TOTAL) iteration(BoolC<true>(), i);
      else iteration(BoolC<false>(), i);
    }
    {
      settle(TOTAL - 1, kprev);
      BAR_SYNC_MINE;
      fence_regs(P); fence_regs(O);
      wg_fence();
      issue_pv(O, P, sV + vs * TILE_BYTES, 1);
      wg_commit();
      BAR_ARRIVE_OTHER;
      wg_wait<0>();
      fence_regs(O);
      pack_o(l0, l1);
      store_o(TILES_PER_CTA - 1);
    }
    if (cw == 0) bar_sync(1, 256);
  }
  asm volatile("barrier.cluster.arrive.relaxed.aligned;\n" ::: "memory");
  asm volatile("barrier.cluster.wait.aligned;\n" ::: "memory");
}

}

typedef CUresult (*EncodeTiledFn)(CUtensorMap*, CUtensorMapDataType, cuuint32_t, void*, const cuuint64_t*, const cuuint64_t*, const cuuint32_t*,
                                  const cuuint32_t*, CUtensorMapInterleave, CUtensorMapSwizzle, CUtensorMapL2promotion, CUtensorMapFloatOOBfill);

extern "C" void kernel_launch(void* const* d_in, const int* in_sizes, int n_in, void* d_out, int out_size) {
  const int* qk = (const int*)d_in[1];
  const int* qv = (const int*)d_in[2];
  const __nv_bfloat16* ks = (const __nv_bfloat16*)d_in[3];
  const __nv_bfloat16* kz = (const __nv_bfloat16*)d_in[4];
  const __nv_bfloat16* vs = (const __nv_bfloat16*)d_in[5];
  const __nv_bfloat16* vz = (const __nv_bfloat16*)d_in[6];
  __nv_bfloat16* out = (__nv_bfloat16*)d_out;
  static EncodeTiledFn encode = nullptr;
  static int fused = 0;
  static uint8_t* scr = nullptr;
  if (!encode) {
    void* sp = nullptr;
    cudaGetSymbolAddress(&sp, g_scratch);
    scr = (uint8_t*)(((uintptr_t)sp + HEAD_STRIDE - 1) & ~(uintptr_t)(HEAD_STRIDE - 1));
    cudaFuncSetAttribute(attn_kernel, cudaFuncAttributeMaxDynamicSharedMemorySize, SMEM_BYTES);
    {
      cudaLaunchConfig_t cfg = {};
      cfg.gridDim = dim3(NCTAS); cfg.blockDim = dim3(384); cfg.dynamicSmemBytes = SMEM_BYTES;
      cudaLaunchAttribute at[1];
      at[0].id = cudaLaunchAttributeClusterDimension; at[0].val.clusterDim.x = CL; at[0].val.clusterDim.y = 1; at[0].val.clusterDim.z = 1;
      cfg.attrs = at; cfg.numAttrs = 1;
      int nc = 0;
      fused = cudaOccupancyMaxActiveClusters(&nc, attn_kernel, &cfg) == cudaSuccess && nc * CL >= NCTAS;
    }
    void* fn = nullptr;
    cudaDriverEntryPointQueryResult qres;
    cudaGetDriverEntryPoint("cuTensorMapEncodeTiled", &fn, cudaEnableDefault, &qres);
    encode = (EncodeTiledFn)fn;
  }
  CUtensorMap tmq;
  {
    const cuuint64_t dims[2] = {(cuuint64_t)DH, (cuuint64_t)HQ * SQ};
    const cuuint64_t strides[1] = {(cuuint64_t)DH * 2};
    const cuuint32_t box[2] = {64, QROWS};
    const cuuint32_t estr[2] = {1, 1};
    encode(&tmq, CU_TENSOR_MAP_DATA_TYPE_BFLOAT16, 2, d_in[0], dims, strides, box, estr, CU_TENSOR_MAP_INTERLEAVE_NONE, CU_TENSOR_MAP_SWIZZLE_128B,
           CU_TENSOR_MAP_L2_PROMOTION_L2_256B, CU_TENSOR_MAP_FLOAT_OOB_FILL_NONE);
  }
  const DqCtx dq = {qk, qv, ks, kz, vs, vz, scr};
  if (!fused) dequant_kernel<<<(2 * HKV * SKV) / (8 * 4), 256>>>(qk, qv, ks, kz, vs, vz, scr);
  attn_kernel<<<NCTAS, 384, SMEM_BYTES>>>(dq, (const __nv_bfloat16*)d_in[0], out, 0u, fused, tmq);
}
```

```cpp
#include <cuda_runtime.h>
#include <cuda.h>
#include <cuda_bf16.h>
#include <stdint.h>

namespace {

constexpr int HQ = 32, HKV = 4, SQ = 2048, SKV = 2048, DH = 128;
constexpr int BN = 128;
constexpr int NBLK = SKV / BN;
constexpr int TILE_BYTES = BN * DH * 2;
constexpr int HALF_BYTES = TILE_BYTES / 2;
#define NK_STAGES 3
#ifndef NV_STAGES
#define NV_STAGES 3
#endif
constexpr int NK = NK_STAGES, NV = NV_STAGES;
constexpr int TILES_PER_CTA = 4;
#define CL 2
constexpr int NCTAS = 128;
#define QROWS 32
#define QFIRST 2
constexpr int QP = 2 * 128 / QROWS;
constexpr int SLICE = (SKV / SKV) * 32768 / CL;
constexpr int SMEM_BYTES = (NK + NV + 1) * TILE_BYTES + 1024 + 256;

constexpr size_t HEAD_STRIDE = 2u << 20, CNT_OFF = 1u << 20;
constexpr int SLICES = 32;
__device__ __align__(1024) uint8_t g_scratch[(HKV + 1) * HEAD_STRIDE];
__device__ __forceinline__ uint8_t* tile_img(uint8_t* scr, int h, int isV, int blk) { return scr + h * HEAD_STRIDE + (size_t)(2 * blk + isV) * TILE_BYTES; }

#define TS(e)
#define ST2(k)

__device__ __forceinline__ uint32_t smem_u32(const void* p) { return (uint32_t)__cvta_generic_to_shared(p); }
__device__ __forceinline__ void wg_fence() { asm volatile("wgmma.fence.sync.aligned;\n" ::: "memory"); }
__device__ __forceinline__ void wg_commit() { asm volatile("wgmma.commit_group.sync.aligned;\n" ::: "memory"); }
template <int N> __device__ __forceinline__ void wg_wait() { asm volatile("wgmma.wait_group.sync.aligned %0;\n" ::"n"(N) : "memory"); }
template <int NR> __device__ __forceinline__ void fence_regs(float (&d)[NR]) {
#pragma unroll
  for (int i = 0; i < NR; i++) asm volatile("" : "+f"(d[i])::"memory");
}
template <int NR> __device__ __forceinline__ void fence_regs(uint32_t (&d)[NR]) {
#pragma unroll
  for (int i = 0; i < NR; i++) asm volatile("" : "+r"(d[i])::"memory");
}
__device__ __forceinline__ void bar_sync(int id, int n) { asm volatile("bar.sync %0, %1;\n" ::"r"(id), "r"(n) : "memory"); }
__device__ __forceinline__ void bar_arrive(int id, int n) { asm volatile("bar.arrive %0, %1;\n" ::"r"(id), "r"(n) : "memory"); }
__device__ __forceinline__ void bar_sync_sel(uint32_t second) {
  asm volatile("{\n.reg .pred p;\nsetp.ne.u32 p, %0, 0;\n@!p bar.sync 1, 256;\n@p bar.sync 2, 256;\n}\n" ::"r"(second) : "memory");
}
__device__ __forceinline__ void bar_arrive_sel(uint32_t second) {
  asm volatile("{\n.reg .pred p;\nsetp.ne.u32 p, %0, 0;\n@!p bar.arrive 1, 256;\n@p bar.arrive 2, 256;\n}\n" ::"r"(second) : "memory");
}
__device__ __forceinline__ void mbar_init(uint32_t bar, uint32_t count) {
  asm volatile("mbarrier.init.shared::cta.b64 [%0], %1;\n" ::"r"(bar), "r"(count) : "memory");
}
__device__ __forceinline__ void mbar_expect_tx(uint32_t bar, uint32_t bytes) {
  asm volatile("mbarrier.arrive.expect_tx.shared::cta.b64 _, [%0], %1;\n" ::"r"(bar), "r"(bytes) : "memory");
}
__device__ __forceinline__ void mbar_wait(uint32_t bar, uint32_t parity) {
  asm volatile(
      "{\n.reg .pred p;\n"
      "WAIT_LOOP:\n"
      "mbarrier.try_wait.parity.shared::cta.b64 p, [%0], %1;\n"
      "@p bra WAIT_DONE;\n"
      "bra WAIT_LOOP;\n"
      "WAIT_DONE:\n}\n" ::"r"(bar), "r"(parity) : "memory");
}
__device__ __forceinline__ uint32_t mbar_test(uint32_t bar, uint32_t parity) {
  uint32_t ok;
  asm volatile("{\n.reg .pred p;\nmbarrier.test_wait.parity.shared::cta.b64 p, [%1], %2;\nselp.u32 %0, 1, 0, p;\n}\n" : "=r"(ok) : "r"(bar), "r"(parity) : "memory");
  return ok;
}
__device__ __forceinline__ void mma_16816(float& c0, float& c1, float& c2, float& c3, uint32_t a0, uint32_t a1, uint32_t a2, uint32_t a3, uint32_t b0, uint32_t b1) {
  asm volatile("mma.sync.aligned.m16n8k16.row.col.f32.bf16.bf16.f32 {%0, %1, %2, %3}, {%4, %5, %6, %7}, {%8, %9}, {%0, %1, %2, %3};\n"
               : "+f"(c0), "+f"(c1), "+f"(c2), "+f"(c3) : "r"(a0), "r"(a1), "r"(a2), "r"(a3), "r"(b0), "r"(b1));
}
__device__ __forceinline__ float rcp_fast(float x) {
  float y;
  asm("rcp.approx.ftz.f32 %0, %1;\n" : "=f"(y) : "f"(x));
  return y;
}
__device__ __forceinline__ void mbar_arrive_local(uint32_t bar) {
  asm volatile("mbarrier.arrive.shared::cta.b64 _, [%0];\n" ::"r"(bar) : "memory");
}
__device__ __forceinline__ void mbar_arrive_cluster(uint32_t bar, uint32_t cta) {
  asm volatile(
      "{\n.reg .b32 ra;\n"
      "mapa.shared::cluster.u32 ra, %0, %1;\n"
      "mbarrier.arrive.shared::cluster.b64 _, [ra];\n}\n" ::"r"(bar), "r"(cta) : "memory");
}
__device__ __forceinline__ void bulk_load_mc(uint32_t dst, const void* src, uint32_t bytes, uint32_t bar, uint16_t mask) {
  asm volatile(
      "cp.async.bulk.shared::cluster.global.mbarrier::complete_tx::bytes.multicast::cluster [%0], [%1], %2, [%3], %4;\n" ::"r"(dst),
      "l"(src), "r"(bytes), "r"(bar), "h"(mask)
      : "memory");
}
__device__ __forceinline__ void bulk_load(uint32_t dst, const void* src, uint32_t bytes, uint32_t bar) {
  asm volatile("cp.async.bulk.shared::cluster.global.mbarrier::complete_tx::bytes [%0], [%1], %2, [%3];\n" ::"r"(dst), "l"(src),
               "r"(bytes), "r"(bar)
               : "memory");
}
__device__ __forceinline__ void tma_load_2d(uint32_t dst, const void* tmap, int c0, int c1, uint32_t bar) {
  asm volatile("cp.async.bulk.tensor.2d.shared::cluster.global.mbarrier::complete_tx::bytes [%0], [%1, {%3, %4}], [%2];\n" ::"r"(dst), "l"(tmap),
               "r"(bar), "r"(c0), "r"(c1)
               : "memory");
}
__device__ __forceinline__ void ldsm_x4(uint32_t& r0, uint32_t& r1, uint32_t& r2, uint32_t& r3, uint32_t addr) {
  asm volatile("ldmatrix.sync.aligned.m8n8.x4.shared.b16 {%0, %1, %2, %3}, [%4];\n" : "=r"(r0), "=r"(r1), "=r"(r2), "=r"(r3) : "r"(addr) : "memory");
}
__device__ __forceinline__ bool wg_any(bool p, int id) {
  uint32_t r;
  asm volatile("{\n.reg .pred p, q;\nsetp.ne.u32 p, %1, 0;\nbarrier.cta.red.or.aligned.pred q, %2, 128, p;\nselp.u32 %0, 1, 0, q;\n}\n"
               : "=r"(r) : "r"((uint32_t)p), "r"(id) : "memory");
  return r != 0;
}
__device__ __forceinline__ float ex2(float x) {
  float y;
  asm("ex2.approx.ftz.f32 %0, %1;\n" : "=f"(y) : "f"(x));
  return y;
}
__device__ __forceinline__ uint32_t pack_bf16(float lo, float hi) {
  uint32_t r;
  asm("cvt.rn.bf16x2.f32 %0, %1, %2;\n" : "=r"(r) : "f"(hi), "f"(lo));
  return r;
}
__device__ __forceinline__ uint64_t make_desc(uint32_t addr, uint32_t lbo, uint32_t sbo) {
  return (uint64_t)((addr & 0x3FFFF) >> 4) | ((uint64_t)(lbo >> 4) << 16) | ((uint64_t)(sbo >> 4) << 32) | (1ull << 62);
}

__device__ __forceinline__ void wgmma_rs_kmaj(float (&d)[64], uint32_t a0, uint32_t a1, uint32_t a2, uint32_t a3, uint64_t descB, int scaleD) {
  asm volatile("{\n.reg .pred p;\nsetp.ne.b32 p, %69, 0;\n"
    "wgmma.mma_async.sync.aligned.m64n128k16.f32.bf16.bf16 "
    "{%0, %1, %2, %3, %4, %5, %6, %7, %8, %9, %10, %11, %12, %13, %14, %15, "
    "%16, %17, %18, %19, %20, %21, %22, %23, %24, %25, %26, %27, %28, %29, %30, %31, "
    "%32, %33, %34, %35, %36, %37, %38, %39, %40, %41, %42, %43, %44, %45, %46, %47, "
    "%48, %49, %50, %51, %52, %53, %54, %55, %56, %57, %58, %59, %60, %61, %62, %63}, "
    "{%64, %65, %66, %67}, %68, p, 1, 1, 0;\n}\n"
    : "+f"(d[0]), "+f"(d[1]), "+f"(d[2]), "+f"(d[3]), "+f"(d[4]), "+f"(d[5]), "+f"(d[6]), "+f"(d[7]),
      "+f"(d[8]), "+f"(d[9]), "+f"(d[10]), "+f"(d[11]), "+f"(d[12]), "+f"(d[13]), "+f"(d[14]), "+f"(d[15]),
      "+f"(d[16]), "+f"(d[17]), "+f"(d[18]), "+f"(d[19]), "+f"(d[20]), "+f"(d[21]), "+f"(d[22]), "+f"(d[23]),
      "+f"(d[24]), "+f"(d[25]), "+f"(d[26]), "+f"(d[27]), "+f"(d[28]), "+f"(d[29]), "+f"(d[30]), "+f"(d[31]),
      "+f"(d[32]), "+f"(d[33]), "+f"(d[34]), "+f"(d[35]), "+f"(d[36]), "+f"(d[37]), "+f"(d[38]), "+f"(d[39]),
      "+f"(d[40]), "+f"(d[41]), "+f"(d[42]), "+f"(d[43]), "+f"(d[44]), "+f"(d[45]), "+f"(d[46]), "+f"(d[47]),
      "+f"(d[48]), "+f"(d[49]), "+f"(d[50]), "+f"(d[51]), "+f"(d[52]), "+f"(d[53]), "+f"(d[54]), "+f"(d[55]),
      "+f"(d[56]), "+f"(d[57]), "+f"(d[58]), "+f"(d[59]), "+f"(d[60]), "+f"(d[61]), "+f"(d[62]), "+f"(d[63])
    : "r"(a0), "r"(a1), "r"(a2), "r"(a3), "l"(descB), "r"(scaleD));
}

__device__ __forceinline__ void wgmma_ss_kmaj(float (&d)[64], uint64_t descA, uint64_t descB, int scaleD) {
  asm volatile("{\n.reg .pred p;\nsetp.ne.b32 p, %66, 0;\n"
    "wgmma.mma_async.sync.aligned.m64n128k16.f32.bf16.bf16 "
    "{%0, %1, %2, %3, %4, %5, %6, %7, %8, %9, %10, %11, %12, %13, %14, %15, "
    "%16, %17, %18, %19, %20, %21, %22, %23, %24, %25, %26, %27, %28, %29, %30, %31, "
    "%32, %33, %34, %35, %36, %37, %38, %39, %40, %41, %42, %43, %44, %45, %46, %47, "
    "%48, %49, %50, %51, %52, %53, %54, %55, %56, %57, %58, %59, %60, %61, %62, %63}, "
    "%64, %65, p, 1, 1, 0, 0;\n}\n"
    : "+f"(d[0]), "+f"(d[1]), "+f"(d[2]), "+f"(d[3]), "+f"(d[4]), "+f"(d[5]), "+f"(d[6]), "+f"(d[7]),
      "+f"(d[8]), "+f"(d[9]), "+f"(d[10]), "+f"(d[11]), "+f"(d[12]), "+f"(d[13]), "+f"(d[14]), "+f"(d[15]),
      "+f"(d[16]), "+f"(d[17]), "+f"(d[18]), "+f"(d[19]), "+f"(d[20]), "+f"(d[21]), "+f"(d[22]), "+f"(d[23]),
      "+f"(d[24]), "+f"(d[25]), "+f"(d[26]), "+f"(d[27]), "+f"(d[28]), "+f"(d[29]), "+f"(d[30]), "+f"(d[31]),
      "+f"(d[32]), "+f"(d[33]), "+f"(d[34]), "+f"(d[35]), "+f"(d[36]), "+f"(d[37]), "+f"(d[38]), "+f"(d[39]),
      "+f"(d[40]), "+f"(d[41]), "+f"(d[42]), "+f"(d[43]), "+f"(d[44]), "+f"(d[45]), "+f"(d[46]), "+f"(d[47]),
      "+f"(d[48]), "+f"(d[49]), "+f"(d[50]), "+f"(d[51]), "+f"(d[52]), "+f"(d[53]), "+f"(d[54]), "+f"(d[55]),
      "+f"(d[56]), "+f"(d[57]), "+f"(d[58]), "+f"(d[59]), "+f"(d[60]), "+f"(d[61]), "+f"(d[62]), "+f"(d[63])
    : "l"(descA), "l"(descB), "r"(scaleD));
}

__device__ __forceinline__ void wgmma_rs_nmaj(float (&d)[64], uint32_t a0, uint32_t a1, uint32_t a2, uint32_t a3, uint64_t descB, int scaleD) {
  asm volatile("{\n.reg .pred p;\nsetp.ne.b32 p, %69, 0;\n"
    "wgmma.mma_async.sync.aligned.m64n128k16.f32.bf16.bf16 "
    "{%0, %1, %2, %3, %4, %5, %6, %7, %8, %9, %10, %11, %12, %13, %14, %15, "
    "%16, %17, %18, %19, %20, %21, %22, %23, %24, %25, %26, %27, %28, %29, %30, %31, "
    "%32, %33, %34, %35, %36, %37, %38, %39, %40, %41, %42, %43, %44, %45, %46, %47, "
    "%48, %49, %50, %51, %52, %53, %54, %55, %56, %57, %58, %59, %60, %61, %62, %63}, "
    "{%64, %65, %66, %67}, %68, p, 1, 1, 1;\n}\n"
    : "+f"(d[0]), "+f"(d[1]), "+f"(d[2]), "+f"(d[3]), "+f"(d[4]), "+f"(d[5]), "+f"(d[6]), "+f"(d[7]),
      "+f"(d[8]), "+f"(d[9]), "+f"(d[10]), "+f"(d[11]), "+f"(d[12]), "+f"(d[13]), "+f"(d[14]), "+f"(d[15]),
      "+f"(d[16]), "+f"(d[17]), "+f"(d[18]), "+f"(d[19]), "+f"(d[20]), "+f"(d[21]), "+f"(d[22]), "+f"(d[23]),
      "+f"(d[24]), "+f"(d[25]), "+f"(d[26]), "+f"(d[27]), "+f"(d[28]), "+f"(d[29]), "+f"(d[30]), "+f"(d[31]),
      "+f"(d[32]), "+f"(d[33]), "+f"(d[34]), "+f"(d[35]), "+f"(d[36]), "+f"(d[37]), "+f"(d[38]), "+f"(d[39]),
      "+f"(d[40]), "+f"(d[41]), "+f"(d[42]), "+f"(d[43]), "+f"(d[44]), "+f"(d[45]), "+f"(d[46]), "+f"(d[47]),
      "+f"(d[48]), "+f"(d[49]), "+f"(d[50]), "+f"(d[51]), "+f"(d[52]), "+f"(d[53]), "+f"(d[54]), "+f"(d[55]),
      "+f"(d[56]), "+f"(d[57]), "+f"(d[58]), "+f"(d[59]), "+f"(d[60]), "+f"(d[61]), "+f"(d[62]), "+f"(d[63])
    : "r"(a0), "r"(a1), "r"(a2), "r"(a3), "l"(descB), "r"(scaleD));
}

struct DqCtx { const int* qk; const int* qv; const __nv_bfloat16 *ks, *kz, *vs, *vz; uint8_t* scr; };
__device__ __forceinline__ float bf_lo(uint32_t u) { return __uint_as_float(u << 16); }
__device__ __forceinline__ float bf_hi(uint32_t u) { return __uint_as_float(u & 0xffff0000u); }
__device__ __forceinline__ float bf_round(float x) { return __bfloat162float(__float2bfloat16_rn(x)); }
__device__ __forceinline__ uint32_t dq_pair_small(uint32_t a, uint32_t b, uint32_t z2, uint32_t ns2) {
  uint32_t r;
  asm("{\n.reg .b32 y, d;\n"
      "mul.rn.bf16x2 y, %1, %4;\n"
      "fma.rn.bf16x2 d, y, %5, %2;\n"
      "mul.rn.bf16x2 %0, d, %3;\n}\n" : "=r"(r) : "r"(a + (b << 16)), "r"(z2), "r"(ns2), "r"(0x7f007f00u), "r"(0xc280c280u));
  return r;
}
template <bool HI> __device__ __forceinline__ uint32_t dq_pair_small1(uint32_t a, uint32_t b, uint32_t z, uint32_t ns) {
  uint32_t r;
  if (HI)
    asm("{\n.reg .b32 y, d, zb, sb;\n.reg .b16 l, h;\n"
        "mov.b32 {l, h}, %2;\nmov.b32 zb, {h, h};\nmov.b32 {l, h}, %3;\nmov.b32 sb, {h, h};\n"
        "mul.rn.bf16x2 y, %1, %4;\n"
        "fma.rn.bf16x2 d, y, %5, zb;\n"
        "mul.rn.bf16x2 %0, d, sb;\n}\n" : "=r"(r) : "r"(a + (b << 16)), "r"(z), "r"(ns), "r"(0x7f007f00u), "r"(0xc280c280u));
  else
    asm("{\n.reg .b32 y, d, zb, sb;\n.reg .b16 l, h;\n"
        "mov.b32 {l, h}, %2;\nmov.b32 zb, {l, l};\nmov.b32 {l, h}, %3;\nmov.b32 sb, {l, l};\n"
        "mul.rn.bf16x2 y, %1, %4;\n"
        "fma.rn.bf16x2 d, y, %5, zb;\n"
        "mul.rn.bf16x2 %0, d, sb;\n}\n" : "=r"(r) : "r"(a + (b << 16)), "r"(z), "r"(ns), "r"(0x7f007f00u), "r"(0xc280c280u));
  return r;
}
__device__ __forceinline__ uint32_t dq_pair_any(int a, int b, uint32_t z2, uint32_t s2) {
  return pack_bf16(bf_round(bf_round((float)a) - bf_lo(z2)) * bf_lo(s2), bf_round(bf_round((float)b) - bf_hi(z2)) * bf_hi(s2));
}
constexpr float SCALE_LOG2 = 0.08838834764831845f * 1.4426950408889634f;
__device__ __forceinline__ uint32_t scale_key(uint32_t k2) {
  uint32_t r;
  asm("{\n.reg .b32 t;\n"
      "mul.rn.bf16x2 t, %1, %2;\n"
      "fma.rn.bf16x2 %0, %1, %3, t;\n}\n" : "=r"(r) : "r"(k2), "r"(0xb9d8b9d8u), "r"(0x3e033e03u));
  return r;
}
struct DqLane {
  uint32_t srcK, srcV, dst;
  int rr0;
  __device__ __forceinline__ DqLane(int cta, int lane) {
    const int j = lane >> 1;
    rr0 = ((cta >> 2) & 7) * 16 + (cta & 3) * 2;
    srcK = (rr0 * DH + lane * 4) * 4;
    srcV = (rr0 * DH + 32 * (j >> 2) + 2 * (j & 3) + 16 * (lane & 1)) * 4;
    dst = (lane >> 4) * HALF_BYTES + rr0 * 128 + (((j ^ rr0) & 7) << 4) + (lane & 1) * 8;
  }
};
template <int OFF> __device__ __forceinline__ void st_v2(uint64_t addr, uint32_t a, uint32_t b) {
  asm volatile("st.global.v2.b32 [%0+%3], {%1, %2};\n" ::"l"(addr), "r"(a), "r"(b), "n"(OFF) : "memory");
}
__device__ __forceinline__ void dq_rows_any(const DqCtx& d, const DqLane& L, bool isV, int blk, int lane) {
  const int j = lane >> 1;
  const int c0 = isV ? 32 * (j >> 2) + 2 * (j & 3) + 16 * (lane & 1) : lane * 4, c1 = isV ? c0 + 8 : c0 + 2;
  const uint64_t dA = reinterpret_cast<uint64_t>(d.scr) + (uint32_t)((blk >> 4) * (uint32_t)HEAD_STRIDE + (2 * (blk & (NBLK - 1)) + isV) * TILE_BYTES + L.dst);
#pragma unroll 1
  for (int i = 0; i < 4; i++) {
    const int tok = blk * BN + L.rr0 + (i & 1) + (i >> 1) * 8;
    const int* src = (isV ? d.qv : d.qk) + (size_t)tok * DH;
    uint32_t za, zb, sa, sb;
    if (isV) {
      za = zb = (uint32_t)__bfloat16_as_ushort(d.vz[tok]) * 0x10001u; sa = sb = (uint32_t)__bfloat16_as_ushort(d.vs[tok]) * 0x10001u;
    } else {
      const uint32_t* zp = reinterpret_cast<const uint32_t*>(d.kz + blk * DH + lane * 4);
      const uint32_t* sp = reinterpret_cast<const uint32_t*>(d.ks + blk * DH + lane * 4);
      za = zp[0]; zb = zp[1]; sa = sp[0]; sb = sp[1];
    }
    uint32_t w0 = dq_pair_any(src[c0], src[c0 + 1], za, sa), w1 = dq_pair_any(src[c1], src[c1 + 1], zb, sb);
    if (!isV) { w0 = scale_key(w0); w1 = scale_key(w1); }
    st_v2<0>((dA ^ ((i & 1) * 0x90)) + (i >> 1) * 1024, w0, w1);
  }
}
struct DqTask {
  uint32_t x[4][4];
  uint32_t z[2], s[2];
  template <bool isV> __device__ __forceinline__ void load(const DqCtx& d, const DqLane& L, int blk, int lane) {
    if (isV) {
      const uint8_t* src = reinterpret_cast<const uint8_t*>(d.qv) + (size_t)(uint32_t)(blk * (BN * DH * 4) + L.srcV);
#pragma unroll
      for (int i = 0; i < 4; i++) {
        const uint8_t* p = src + ((i & 1) + (i >> 1) * 8) * (DH * 4);
        const int2 a = __ldcs(reinterpret_cast<const int2*>(p)), b = __ldcs(reinterpret_cast<const int2*>(p + 32));
        x[i][0] = a.x; x[i][1] = a.y; x[i][2] = b.x; x[i][3] = b.y;
      }
      const uint32_t* zp = reinterpret_cast<const uint32_t*>(d.vz + blk * BN + L.rr0);
      const uint32_t* sp = reinterpret_cast<const uint32_t*>(d.vs + blk * BN + L.rr0);
      z[0] = __ldg(zp); z[1] = __ldg(zp + 4); s[0] = __ldg(sp); s[1] = __ldg(sp + 4);
    } else {
      const uint8_t* src = reinterpret_cast<const uint8_t*>(d.qk) + (size_t)(uint32_t)(blk * (BN * DH * 4) + L.srcK);
#pragma unroll
      for (int i = 0; i < 4; i++) {
        const int4 a = __ldcs(reinterpret_cast<const int4*>(src + ((i & 1) + (i >> 1) * 8) * (DH * 4)));
        x[i][0] = a.x; x[i][1] = a.y; x[i][2] = a.z; x[i][3] = a.w;
      }
      const uint32_t o = blk * (DH * 2) + lane * 8;
      const uint2 zz = __ldg(reinterpret_cast<const uint2*>(reinterpret_cast<const uint8_t*>(d.kz) + o));
      const uint2 ss = __ldg(reinterpret_cast<const uint2*>(reinterpret_cast<const uint8_t*>(d.ks) + o));
      z[0] = zz.x; z[1] = zz.y; s[0] = ss.x; s[1] = ss.y;
    }
  }
  template <bool isV> __device__ __forceinline__ bool store(const DqCtx& d, const DqLane& L, int blk) const {
    uint32_t any = 0;
#pragma unroll
    for (int i = 0; i < 4; i++) any |= x[i][0] | x[i][1] | x[i][2] | x[i][3];
    if (__builtin_expect(__any_sync(0xffffffffu, any >= 256u), 0)) return true;
    const uint64_t dA = reinterpret_cast<uint64_t>(d.scr) + (uint32_t)((blk >> 4) * (uint32_t)HEAD_STRIDE + (2 * (blk & (NBLK - 1)) + isV) * TILE_BYTES + L.dst);
    const uint64_t dB = dA ^ 0x90;
    const uint32_t ns0 = s[0] ^ 0x80008000u, ns1 = s[1] ^ 0x80008000u;
    if (isV) {
      st_v2<0>(dA, dq_pair_small1<false>(x[0][0], x[0][1], z[0], ns0), dq_pair_small1<false>(x[0][2], x[0][3], z[0], ns0));
      st_v2<0>(dB, dq_pair_small1<true>(x[1][0], x[1][1], z[0], ns0), dq_pair_small1<true>(x[1][2], x[1][3], z[0], ns0));
      st_v2<1024>(dA, dq_pair_small1<false>(x[2][0], x[2][1], z[1], ns1), dq_pair_small1<false>(x[2][2], x[2][3], z[1], ns1));
      st_v2<1024>(dB, dq_pair_small1<true>(x[3][0], x[3][1], z[1], ns1), dq_pair_small1<true>(x[3][2], x[3][3], z[1], ns1));
    } else {
      st_v2<0>(dA, scale_key(dq_pair_small(x[0][0], x[0][1], z[0], ns0)), scale_key(dq_pair_small(x[0][2], x[0][3], z[1], ns1)));
      st_v2<0>(dB, scale_key(dq_pair_small(x[1][0], x[1][1], z[0], ns0)), scale_key(dq_pair_small(x[1][2], x[1][3], z[1], ns1)));
      st_v2<1024>(dA, scale_key(dq_pair_small(x[2][0], x[2][1], z[0], ns0)), scale_key(dq_pair_small(x[2][2], x[2][3], z[1], ns1)));
      st_v2<1024>(dB, scale_key(dq_pair_small(x[3][0], x[3][1], z[0], ns0)), scale_key(dq_pair_small(x[3][2], x[3][3], z[1], ns1)));
    }
    return false;
  }
};
__device__ __forceinline__ unsigned* tile_cnt(uint8_t* scr, int h, int t) { return reinterpret_cast<unsigned*>(scr + h * HEAD_STRIDE + CNT_OFF) + t * 32; }
__device__ __forceinline__ void dq_publish(unsigned* cnt, int lane) {
  asm volatile("fence.proxy.async.global;\n" ::: "memory");
  __syncwarp();
  if (lane == 0) asm volatile("red.release.gpu.global.add.u32 [%0], 1;\n" ::"l"(cnt) : "memory");
}

__global__ void __launch_bounds__(256) dequant_kernel(const int* __restrict__ qk, const int* __restrict__ qv,
                                                      const __nv_bfloat16* __restrict__ ks, const __nv_bfloat16* __restrict__ kz,
                                                      const __nv_bfloat16* __restrict__ vs, const __nv_bfloat16* __restrict__ vz, uint8_t* scr) {
  constexpr int ROWS_PER_WARP = 4;
  const int lane = threadIdx.x & 31;
  const int warp = blockIdx.x * 8 + (threadIdx.x >> 5);
  const int row0 = warp * ROWS_PER_WARP;
  const bool isV = row0 >= HKV * SKV;
  const int r0 = isV ? row0 - HKV * SKV : row0;
  const int* src = (isV ? qv : qk) + (size_t)r0 * DH + lane * 4;
  int4 x[ROWS_PER_WARP];
#pragma unroll
  for (int i = 0; i < ROWS_PER_WARP; i++) x[i] = __ldcs(reinterpret_cast<const int4*>(src + i * DH));
  float z[4], s[4];
  if (!isV) {
    const int g = r0 / BN;
    const uint2 zz = *reinterpret_cast<const uint2*>(kz + (size_t)g * DH + lane * 4);
    const uint2 ss = *reinterpret_cast<const uint2*>(ks + (size_t)g * DH + lane * 4);
    z[0] = __uint_as_float(zz.x << 16); z[1] = __uint_as_float(zz.x & 0xffff0000u);
    z[2] = __uint_as_float(zz.y << 16); z[3] = __uint_as_float(zz.y & 0xffff0000u);
    s[0] = __uint_as_float(ss.x << 16); s[1] = __uint_as_float(ss.x & 0xffff0000u);
    s[2] = __uint_as_float(ss.y << 16); s[3] = __uint_as_float(ss.y & 0xffff0000u);
  }
  uint8_t* img = tile_img(scr, r0 / SKV, isV, (r0 / BN) & (NBLK - 1));
  const int J = lane >> 3, c = (lane & 7) >> 1, sb = lane & 1;
  const int j = 4 * J + 2 * sb + (c & 1);
  const int half = j >> 3, ch = j & 7;
#pragma unroll
  for (int i = 0; i < ROWS_PER_WARP; i++) {
    const int r = r0 + i;
    if (isV) {
      const float zv = __bfloat162float(vz[r]), sv = __bfloat162float(vs[r]);
#pragma unroll
      for (int e = 0; e < 4; e++) { z[e] = zv; s[e] = sv; }
    }
    const int xi[4] = {x[i].x, x[i].y, x[i].z, x[i].w};
    float o[4];
#pragma unroll
    for (int e = 0; e < 4; e++) {
      const float qf = __bfloat162float(__float2bfloat16_rn((float)xi[e]));
      const float df = __bfloat162float(__float2bfloat16_rn(qf - z[e]));
      o[e] = df * s[e];
    }
    const uint32_t p0 = pack_bf16(o[0], o[1]), p1 = pack_bf16(o[2], o[3]);
    const int rr = r & (BN - 1);
    uint2 w;
    if (isV) {
      const uint32_t send = (c & 1) ? p0 : p1;
      const uint32_t recv = __shfl_xor_sync(0xffffffffu, send, 2);
      if (c & 1) { w.x = recv; w.y = p1; } else { w.x = p0; w.y = recv; }
      *reinterpret_cast<uint2*>(img + half * HALF_BYTES + rr * 128 + ((ch ^ (rr & 7)) << 4) + (c >> 1) * 8) = w;
    } else {
      w.x = scale_key(p0); w.y = scale_key(p1);
      *reinterpret_cast<uint2*>(img + (lane >> 4) * HALF_BYTES + rr * 128 + ((((lane >> 1) & 7) ^ (rr & 7)) << 4) + (lane & 1) * 8) = w;
    }
  }
}

#define SPLIT 5
#define DEPD 2
constexpr float SUM_LO = 5.9604644775390625e-8f, SUM_HI = 1099511627776.0f;

__device__ __forceinline__ void issue_qk(float (&S)[64], const uint32_t (&Q)[32], uint32_t kaddr) {
  const uint64_t d0 = make_desc(kaddr, 16, 1024);
#pragma unroll
  for (int k = 0; k < 8; k++)
    wgmma_rs_kmaj(S, Q[4 * k], Q[4 * k + 1], Q[4 * k + 2], Q[4 * k + 3], d0 + (uint64_t)(((k & 3) * 32 + (k >> 2) * HALF_BYTES) >> 4), k != 0);
}
__device__ __forceinline__ void issue_qk_ss(float (&S)[64], uint32_t qaddr, uint32_t kaddr) {
  const uint64_t a0 = make_desc(qaddr, 16, 1024), d0 = make_desc(kaddr, 16, 1024);
#pragma unroll
  for (int k = 0; k < 8; k++) {
    const uint64_t off = (uint64_t)(((k & 3) * 32 + (k >> 2) * HALF_BYTES) >> 4);
    wgmma_ss_kmaj(S, a0 + off, d0 + off, k != 0);
  }
}
__device__ __forceinline__ void issue_pv(float (&O)[64], const uint32_t (&P)[32], uint32_t vaddr, int acc) {
  const uint64_t d0 = make_desc(vaddr, HALF_BYTES, 1024);
#pragma unroll
  for (int k = 0; k < 8; k++)
    wgmma_rs_nmaj(O, P[4 * k], P[4 * k + 1], P[4 * k + 2], P[4 * k + 3], d0 + (uint64_t)((k * 2048) >> 4), (k != 0) | acc);
}
__device__ __forceinline__ float tie(float a, float b, uint32_t z) {
  uint32_t r;
  asm("lop3.b32 %0, %1, %2, %3, 0xF8;\n" : "=r"(r) : "r"(__float_as_uint(a)), "r"(__float_as_uint(b)), "r"(z));
  return __uint_as_float(r);
}

__device__ __forceinline__ uint32_t tieu(uint32_t a, float b, uint32_t z) {
  uint32_t r;
  asm("lop3.b32 %0, %1, %2, %3, 0xF8;\n" : "=r"(r) : "r"(a), "r"(__float_as_uint(b)), "r"(z));
  return r;
}

#define BAR_SYNC_MINE bar_sync(my_bar, 256)
#define BAR_ARRIVE_OTHER bar_arrive(other_bar, 256)
#define LDSM_POS 0
template <bool B> struct BoolC { static constexpr bool value = B; };

#define QMODE 0
#define EARLY_NEXT
#define Q_DELAY 300
#define Q_DELAY1 Q_DELAY
#define NPRE 1
#define POLLW 4
#define PDEPTH 1
__global__ void __cluster_dims__(CL, 1, 1) __launch_bounds__(384, 1)
attn_kernel(const DqCtx dq, const __nv_bfloat16* __restrict__ q, __nv_bfloat16* __restrict__ out, const uint32_t zero, const int fused,
            const __grid_constant__ CUtensorMap tmq) {
  extern __shared__ uint8_t smem_raw[];
  const uint32_t sbase = (smem_u32(smem_raw) + 1023u) & ~1023u;
  const uint32_t sK = sbase, sV = sbase + NK * TILE_BYTES, sQ = sbase + (NK + NV) * TILE_BYTES;
  const uint32_t bars = sbase + (NK + NV + 1) * TILE_BYTES;
  const uint32_t fullK = bars, fullV = bars + 8 * NK, emptyK = bars + 8 * (NK + NV), emptyV = emptyK + 8 * NK;
  const uint32_t fullQ = emptyV + 8 * NV, emptyQ = fullQ + 8, fullR = emptyQ + 8;

  const int cta = blockIdx.x;
  const int warp = __shfl_sync(0xffffffffu, (int)(threadIdx.x >> 5), 0);
  const int lane = threadIdx.x & 31;
  const int wg = warp >> 2;
  const uint32_t rank = cta & (CL - 1);
  const int h = cta >> 5;
  const int row0 = cta * (TILES_PER_CTA * 128);
  constexpr int TOTAL = TILES_PER_CTA * NBLK;

  const DqLane L(cta, lane);
  DqTask task;
  uint32_t todo = 0;
  if (warp >= 4) {
    uint4 q0[8];
    asm volatile("barrier.cluster.arrive.relaxed.aligned;\n" ::: "memory");
    if (Q_DELAY + Q_DELAY1 > 0) { const uint32_t t0 = clock(); while ((uint32_t)clock() - t0 < (warp >= 8 ? Q_DELAY1 : Q_DELAY)) { } }
    const __nv_bfloat16* qs = q + (size_t)(row0 + (warp - 4) * 16 + (lane >> 4)) * DH + (lane & 15) * 8;
#pragma unroll
    for (int i = 0; i < 8; i++) {
      q0[i] = __ldcs(reinterpret_cast<const uint4*>(qs + 2 * i * DH));
    }
#pragma unroll
    for (int i = 0; i < 8; i++) {
      const int rr = (warp - 4) * 16 + 2 * i + (lane >> 4);
      asm volatile("st.shared.v4.b32 [%0], {%1, %2, %3, %4};\n" ::"r"(sQ + ((lane >> 3) & 1) * HALF_BYTES + rr * 128 + (((lane ^ rr) & 7) << 4)),
                   "r"(q0[i].x), "r"(q0[i].y), "r"(q0[i].z), "r"(q0[i].w) : "memory");
    }
    asm volatile("fence.proxy.async.shared::cta;\n" ::: "memory");
  } else if (warp == 3) {
    ST2(0);
    if (lane == 0) {
      for (int s = 0; s < NK; s++) { mbar_init(fullK + 8 * s, 1); mbar_init(emptyK + 8 * s, 8 * CL); }
      for (int s = 0; s < NV; s++) { mbar_init(fullV + 8 * s, 1); mbar_init(emptyV + 8 * s, 8 * CL); }
      mbar_init(fullQ, 1); mbar_init(emptyQ, 8); mbar_init(fullR, 1); mbar_init(fullR + 8, 1);
      asm volatile("fence.mbarrier_init.release.cluster;\n" ::: "memory");
    }
    __syncwarp();
    asm volatile("barrier.cluster.arrive.relaxed.aligned;\n" ::: "memory");
    ST2(1);
  } else {
    asm volatile("barrier.cluster.arrive.relaxed.aligned;\n" ::: "memory");
    if (fused) {
      if (warp < 2) task.load<false>(dq, L, h * NBLK + warp, lane); else task.load<true>(dq, L, h * NBLK, lane);
      const int t0 = warp < 2 ? 2 * warp : 1;
      if (warp < 2 ? task.store<false>(dq, L, h * NBLK + warp) : task.store<true>(dq, L, h * NBLK)) todo = 1u << t0;
      task.load<true>(dq, L, h * NBLK + 1 + warp, lane);
      asm volatile("fence.proxy.async.global;\n" ::: "memory");
      __syncwarp();
      if (lane == 0 && !todo) asm volatile("red.release.gpu.global.add.u32 [%0], 1;\n" ::"l"(tile_cnt(dq.scr, h, t0)) : "memory");
    }
  }
  asm volatile("barrier.cluster.wait.aligned;\n" ::: "memory");

  if (wg == 0) {
    if (warp == 3) ST2(2);
    asm volatile("setmaxnreg.dec.sync.aligned.u32 40;\n");
    if (warp == 3) {
      ST2(3);
      const uint8_t* img = dq.scr + h * HEAD_STRIDE + rank * SLICE;
      const unsigned* cnt = tile_cnt(dq.scr, h, lane);
      uint32_t ready = fused ? 0u : ~0u;
      auto need = [&](int t) {
        if ((ready >> t) & 1) return;
        unsigned n = 0;
        do {
          unsigned v = 0;
          if ((unsigned)(lane - (t - 1)) < POLLW) asm volatile("ld.acquire.gpu.global.u32 %0, [%1];\n" : "=r"(v) : "l"(cnt) : "memory");
          ready |= __ballot_sync(0xffffffffu, v >= SLICES);
          if (++n > (1u << 24)) __trap();
        } while (!((ready >> t) & 1));
        __syncwarp();
        asm volatile("fence.proxy.async.global;\n" ::: "memory");
      };
      int ks = 0, kph = 1, vs = 0, vph = 1;
      for (int i = 0; i <= TOTAL; i++) {
        if (i < TOTAL) {
          mbar_wait(emptyK + 8 * ks, kph);
          if (i < NBLK) need(2 * i);
          if (lane == 0) {
            mbar_expect_tx(fullK + 8 * ks, TILE_BYTES);
            bulk_load_mc(sK + ks * TILE_BYTES + rank * SLICE, img + (size_t)(i & (NBLK - 1)) * (2 * TILE_BYTES), SLICE, fullK + 8 * ks, (uint16_t)((1 << CL) - 1));
          }
          if (i < 2) ST2(4 + 2 * i);
          if (++ks == NK) { ks = 0; kph ^= 1; }
        }
        if (i > 0) {
          mbar_wait(emptyV + 8 * vs, vph);
          if (i <= NBLK) need(2 * i - 1);
          if (i == 1) ST2(7);
          if (lane == 0) {
            mbar_expect_tx(fullV + 8 * vs, TILE_BYTES);
            bulk_load_mc(sV + vs * TILE_BYTES + rank * SLICE, img + (size_t)((i - 1) & (NBLK - 1)) * (2 * TILE_BYTES) + TILE_BYTES, SLICE, fullV + 8 * vs, (uint16_t)((1 << CL) - 1));
          }
          if (i == 1) ST2(8);
          if (++vs == NV) { vs = 0; vph ^= 1; }
        }
        const int p = (i & (NBLK - 1)) - QFIRST;
        if (p >= 0 && p < QP && i < TOTAL - NBLK) {
          if (p == 0) {
            mbar_wait(emptyQ, ((i >> 4) & 1));
            if (lane == 0) mbar_expect_tx(fullQ, TILE_BYTES);
          }
          if (lane == 0) tma_load_2d(sQ + (p & 1) * HALF_BYTES + (p >> 1) * (QROWS * 128), &tmq, (p & 1) * 64, row0 + ((i >> 4) + 1) * 128 + (p >> 1) * QROWS, fullQ);
        }
      }
      if (fused) {
        unsigned* done = reinterpret_cast<unsigned*>(dq.scr + CNT_OFF) + 2 * NBLK * 32;
        unsigned last = 0;
        if (lane == 0) last = atomicAdd(done, 1u) == NCTAS - 1;
        if (__shfl_sync(0xffffffffu, last, 0)) {
#pragma unroll
          for (int k = 0; k < HKV; k++) *tile_cnt(dq.scr, k, lane) = 0;
          if (lane == 0) *done = 0;
        }
      }
    } else if (fused) {
#pragma unroll 1
      for (int b = 2 + warp; b <= NBLK; b += 3) {
        if (task.store<true>(dq, L, h * NBLK + b - 1)) todo |= 1u << (2 * b - 1);
        if (b < NBLK) {
          task.load<false>(dq, L, h * NBLK + b, lane);
          if (task.store<false>(dq, L, h * NBLK + b)) todo |= 1u << (2 * b);
        }
        if (b + 3 <= NBLK) task.load<true>(dq, L, h * NBLK + b + 2, lane);
        asm volatile("fence.proxy.async.global;\n" ::: "memory");
        __syncwarp();
        if (lane < (b < NBLK ? 2 : 1) && !((todo >> (2 * b - 1 + lane)) & 1)) asm volatile("red.release.gpu.global.add.u32 [%0], 1;\n" ::"l"(tile_cnt(dq.scr, h, 2 * b - 1 + lane)) : "memory");
      }
#pragma unroll 1
      while (__builtin_expect(todo != 0, 0)) {
        const int t = __ffs(todo) - 1;
        todo &= todo - 1;
        dq_rows_any(dq, L, t & 1, h * NBLK + (t >> 1), lane);
        dq_publish(tile_cnt(dq.scr, h, t), lane);
      }
    }
    __syncwarp();
    asm volatile("barrier.cluster.arrive.relaxed.aligned;\n" ::: "memory");
  } else {
    asm volatile("setmaxnreg.inc.sync.aligned.u32 232;\n");
    uint32_t tid;
    asm volatile("mov.u32 %0, %%tid.x;\n" : "=r"(tid));
    const int my_bar = tid >> 7, other_bar = 3 - my_bar;
    const int cw = my_bar - 1;
    const int wq = (tid >> 5) & 3;
    const int c = lane & 3;
    const int myrow = row0 + cw * 64 + wq * 16 + (lane >> 2);
    __nv_bfloat16* optr = out + (size_t)myrow * DH + 8 * c;
    const uint32_t qaddr = sQ + (cw * 64 + wq * 16 + (lane & 15)) * 128 + ((((lane >> 4) ^ lane) & 7) << 4);

    float S[64], O[64];
    uint32_t P[32], Q[32];
    float l0 = 0.f, l1 = 0.f;
    float s0, s1;
    uint32_t bad = 0;
#pragma unroll
    for (int i = 0; i < 64; i++) { S[i] = 0.f; O[i] = 0.f; }

    auto ldsm_q = [&]() {
#pragma unroll
      for (int k = 0; k < 8; k++) ldsm_x4(Q[4 * k], Q[4 * k + 1], Q[4 * k + 2], Q[4 * k + 3], (qaddr ^ ((k & 3) << 5)) + (k >> 2) * HALF_BYTES);
    };
    auto release = [&](uint32_t bar) {
      if (lane < CL) mbar_arrive_cluster(bar, lane);
    };
    auto exps = [&](float (&hist)[8][2]) {
#pragma unroll
      for (int k = 0; k < 8; k++) {
        float a0 = k ? hist[k - 1][0] : 0.f, a1 = k ? hist[k - 1][1] : 0.f;
#pragma unroll
        for (int j = 2 * k; j < 2 * k + 2; j++) {
          S[4 * j + 0] = ex2(S[4 * j + 0]); S[4 * j + 1] = ex2(S[4 * j + 1]); S[4 * j + 2] = ex2(S[4 * j + 2]); S[4 * j + 3] = ex2(S[4 * j + 3]);
          if (j == 0) { a0 = S[0] + S[1]; a1 = S[2] + S[3]; }
          else { a0 += S[4 * j + 0]; a0 += S[4 * j + 1]; a1 += S[4 * j + 2]; a1 += S[4 * j + 3]; }
        }
        hist[k][0] = a0; hist[k][1] = a1;
      }
    };
    auto convert_p = [&]() {
#pragma unroll
      for (int i = 0; i < 32; i++) P[i] = pack_bf16(S[2 * i], S[2 * i + 1]);
    };
    auto pack_o = [&](float r0, float r1) {
#pragma unroll
      for (int J = 0; J < 4; J++) {
        float* o = &O[16 * J];
        asm volatile("{\n.reg .f32 t<16>;\n.reg .b32 u<8>;\n"
            "mul.f32 t0, %0, %16;\nmul.f32 t1, %1, %16;\nmul.f32 t2, %2, %17;\nmul.f32 t3, %3, %17;\n"
            "mul.f32 t4, %4, %16;\nmul.f32 t5, %5, %16;\nmul.f32 t6, %6, %17;\nmul.f32 t7, %7, %17;\n"
            "mul.f32 t8, %8, %16;\nmul.f32 t9, %9, %16;\nmul.f32 t10, %10, %17;\nmul.f32 t11, %11, %17;\n"
            "mul.f32 t12, %12, %16;\nmul.f32 t13, %13, %16;\nmul.f32 t14, %14, %17;\nmul.f32 t15, %15, %17;\n"
            "cvt.rn.bf16x2.f32 u0, t1, t0;\ncvt.rn.bf16x2.f32 u1, t5, t4;\ncvt.rn.bf16x2.f32 u2, t9, t8;\ncvt.rn.bf16x2.f32 u3, t13, t12;\n"
            "cvt.rn.bf16x2.f32 u4, t3, t2;\ncvt.rn.bf16x2.f32 u5, t7, t6;\ncvt.rn.bf16x2.f32 u6, t11, t10;\ncvt.rn.bf16x2.f32 u7, t15, t14;\n"
            "mov.b32 %0, u0;\nmov.b32 %1, u1;\nmov.b32 %2, u2;\nmov.b32 %3, u3;\n"
            "mov.b32 %4, u4;\nmov.b32 %5, u5;\nmov.b32 %6, u6;\nmov.b32 %7, u7;\n}\n"
            : "+f"(o[0]), "+f"(o[1]), "+f"(o[2]), "+f"(o[3]), "+f"(o[4]), "+f"(o[5]), "+f"(o[6]), "+f"(o[7]),
              "+f"(o[8]), "+f"(o[9]), "+f"(o[10]), "+f"(o[11]), "+f"(o[12]), "+f"(o[13]), "+f"(o[14]), "+f"(o[15])
            : "f"(r0), "f"(r1));
      }
    };
    auto store_o = [&](int tile) {
      __nv_bfloat16* o = optr + (size_t)tile * 128 * DH;
#pragma unroll
      for (int J = 0; J < 4; J++) {
        asm volatile("st.global.v4.b32 [%0], {%1, %2, %3, %4};\n" :: "l"(o + 32 * J), "f"(O[16 * J]), "f"(O[16 * J + 1]), "f"(O[16 * J + 2]), "f"(O[16 * J + 3]) : "memory");
        asm volatile("st.global.v4.b32 [%0], {%1, %2, %3, %4};\n" :: "l"(o + 8 * DH + 32 * J), "f"(O[16 * J + 4]), "f"(O[16 * J + 5]), "f"(O[16 * J + 6]), "f"(O[16 * J + 7]) : "memory");
      }
    };
#define EPI_MODE 0
#define STORE_AT_SETTLE { pack_o(l0, l1); store_o((i >> 4) - 1); }
    auto finish_sums = [&]() {
      l0 += __shfl_xor_sync(0xffffffffu, l0, 1); l1 += __shfl_xor_sync(0xffffffffu, l1, 1);
      l0 += __shfl_xor_sync(0xffffffffu, l0, 2); l1 += __shfl_xor_sync(0xffffffffu, l1, 2);
      const bool ok = l0 >= SUM_LO && l0 <= SUM_HI && l1 >= SUM_LO && l1 <= SUM_HI;
      l0 = rcp_fast(l0); l1 = rcp_fast(l1);
      return ok;
    };
    auto settle = [&](int i) {
      const int blk = i & (NBLK - 1);
      if (blk == 0) {
        if (i > 0) STORE_AT_SETTLE;
        l0 = 0.f; l1 = 0.f;
      }
      l0 += s0; l1 += s1;
      if (blk == NBLK - 1) { if (!finish_sums()) bad |= 1u << (i >> 4); }
    };

    int ks = 0, kph = 0, vs = 0, vph = 0;
    if (cw == 1) bar_arrive(1, 256);
    __syncwarp();
    ldsm_q();

    {
      if (warp == 4) ST2(9);
      mbar_wait(fullK, 0);
      if (warp == 4) ST2(10);
      BAR_SYNC_MINE;
      fence_regs(Q); fence_regs(S);
      wg_fence();
      issue_qk(S, Q, sK);
      wg_commit();
      BAR_ARRIVE_OTHER;
      if (lane == 0) mbar_arrive_local(emptyQ);
      ks = 1;
      if (warp == 4) ST2(11);
      wg_wait<0>();
      fence_regs(S);
      if (warp == 4) ST2(12);
      release(emptyK);
      float hist[8][2];
      exps(hist);
      convert_p();
      s0 = hist[7][0]; s1 = hist[7][1];
      if (warp == 4) ST2(13);
      mbar_wait(fullK + 8 * ks, kph);
      if (warp == 4) ST2(14);
      mbar_wait(fullV + 8 * vs, vph);
      if (warp == 4) ST2(15);
    }
    auto iteration = [&](auto pre_c, int i) {
      constexpr bool PRE = decltype(pre_c)::value;
      const int blk = PRE ? NBLK - 2 : (i & (NBLK - 1));
      const uint32_t kaddr = sK + ks * TILE_BYTES, vaddr = sV + vs * TILE_BYTES;
      const uint32_t relK = emptyK + 8 * ks, relV = emptyV + 8 * vs;
      if (++ks == NK) { ks = 0; kph ^= 1; }
      if (++vs == NV) { vs = 0; vph ^= 1; }
      const uint32_t nextK = fullK + 8 * ks, nextV = fullV + 8 * vs;
      BAR_SYNC_MINE;
      fence_regs(Q); fence_regs(S);
      wg_fence();
      issue_qk(S, Q, kaddr);
      wg_commit();
      settle(i);
      fence_regs(P); fence_regs(O);
      wg_fence();
      issue_pv(O, P, vaddr, blk != 0);
      wg_commit();
      BAR_ARRIVE_OTHER;
      if (PRE) mbar_wait(fullQ, (((i + 2) >> 4) & 1) ^ 1);
      else if (blk == NBLK - 1 && lane == 0) mbar_arrive_local(emptyQ);
      wg_wait<1>();
      fence_regs(S); fence_regs(Q);
      release(relK);
      if (PRE) { if (LDSM_POS == 0) ldsm_q(); }
      float hist[8][2];
      exps(hist);
      const uint32_t tK = mbar_test(nextK, tieu(kph, hist[SPLIT - 1][0], zero));
      const uint32_t tV = mbar_test(nextV, tieu(vph, hist[SPLIT - 1][1], zero));
      wg_wait<0>();
      const bool okK = __all_sync(0xffffffffu, tK) || (i + 2 >= TOTAL);
      const bool okV = __all_sync(0xffffffffu, tV);
      fence_regs(O); fence_regs(P);
      release(relV);
      convert_p();
      s0 = hist[7][0]; s1 = hist[7][1];
      if (PRE && LDSM_POS == 1) ldsm_q();
      if (!PRE && blk == NBLK - 1) {
      }
      if (!okK) mbar_wait(nextK, kph);
      if (!okV) mbar_wait(nextV, vph);
    };
#pragma unroll 1
    for (int i = 0; i < TOTAL - 1; i++) {
      if ((i & (NBLK - 1)) == NBLK - 2 && i + 2 < TOTAL) iteration(BoolC<true>(), i);
      else iteration(BoolC<false>(), i);
    }
    asm volatile("barrier.cluster.arrive.relaxed.aligned;\n" ::: "memory");
    {
      settle(TOTAL - 1);
      BAR_SYNC_MINE;
      fence_regs(P); fence_regs(O);
      wg_fence();
      issue_pv(O, P, sV + vs * TILE_BYTES, 1);
      wg_commit();
      BAR_ARRIVE_OTHER;
      const bool redo = wg_any(bad != 0, 5 + cw);
      wg_wait<0>();
      fence_regs(O);
      pack_o(l0, l1);
      store_o(TILES_PER_CTA - 1);
      if (cw == 0) bar_sync(1, 256);
      if (__builtin_expect(redo, 0)) {
        static_assert(NK >= 3 && NV >= 3 && TOTAL % NK == 1 && TOTAL % NV == 1, "the last block uses stage 0");
        const uint32_t kaddr = sK + (1 + cw) * TILE_BYTES, vaddr = sV + (1 + cw) * TILE_BYTES, bar = fullR + 8 * cw;
        const uint8_t* img = dq.scr + h * HEAD_STRIDE;
        uint32_t ph = 0;
#pragma unroll 1
        for (int tile = 0; tile < TILES_PER_CTA; tile++) {
          if (!wg_any((bad >> tile) & 1, 5 + cw)) continue;
          const uint32_t* qp = reinterpret_cast<const uint32_t*>(q + ((size_t)myrow + tile * 128) * DH) + c;
          float m0 = 0.f, m1 = 0.f;
#pragma unroll 1
          for (int blk = 0; blk < NBLK; blk++) {
#pragma unroll
            for (int k = 0; k < 8; k++) {
              Q[4 * k] = __ldg(qp + 8 * k); Q[4 * k + 1] = __ldg(qp + 8 * k + 4 * DH); Q[4 * k + 2] = __ldg(qp + 8 * k + 4); Q[4 * k + 3] = __ldg(qp + 8 * k + 4 + 4 * DH);
            }
            if ((tid & 127) == 0) {
              asm volatile("fence.proxy.async.global;\n" ::: "memory");
              mbar_expect_tx(bar, 2 * TILE_BYTES);
              bulk_load(kaddr, img + (size_t)blk * (2 * TILE_BYTES), TILE_BYTES, bar);
              bulk_load(vaddr, img + (size_t)blk * (2 * TILE_BYTES) + TILE_BYTES, TILE_BYTES, bar);
            }
            mbar_wait(bar, ph);
            ph ^= 1;
            fence_regs(Q); fence_regs(S);
            wg_fence();
            issue_qk(S, Q, kaddr);
            wg_commit();
            wg_wait<0>();
            fence_regs(S); fence_regs(Q);
            float x0 = fmaxf(S[0], S[1]), x1 = fmaxf(S[2], S[3]);
#pragma unroll
            for (int j = 1; j < 16; j++) { x0 = fmaxf(x0, fmaxf(S[4 * j], S[4 * j + 1])); x1 = fmaxf(x1, fmaxf(S[4 * j + 2], S[4 * j + 3])); }
            x0 = fmaxf(x0, __shfl_xor_sync(0xffffffffu, x0, 1)); x1 = fmaxf(x1, __shfl_xor_sync(0xffffffffu, x1, 1));
            x0 = fmaxf(x0, __shfl_xor_sync(0xffffffffu, x0, 2)); x1 = fmaxf(x1, __shfl_xor_sync(0xffffffffu, x1, 2));
            x0 = fmaxf(x0, -3.0e38f); x1 = fmaxf(x1, -3.0e38f);
            if (blk == 0) { l0 = 0.f; l1 = 0.f; }
            else {
              x0 = fmaxf(x0, m0); x1 = fmaxf(x1, m1);
              const float a0 = ex2(m0 - x0), a1 = ex2(m1 - x1);
              l0 *= a0; l1 *= a1;
#pragma unroll
              for (int j = 0; j < 16; j++) { O[4 * j] *= a0; O[4 * j + 1] *= a0; O[4 * j + 2] *= a1; O[4 * j + 3] *= a1; }
            }
            m0 = x0; m1 = x1;
#pragma unroll
            for (int j = 0; j < 16; j++) {
              S[4 * j] = ex2(S[4 * j] - m0); S[4 * j + 1] = ex2(S[4 * j + 1] - m0); S[4 * j + 2] = ex2(S[4 * j + 2] - m1); S[4 * j + 3] = ex2(S[4 * j + 3] - m1);
              l0 += S[4 * j] + S[4 * j + 1]; l1 += S[4 * j + 2] + S[4 * j + 3];
            }
            convert_p();
            fence_regs(P); fence_regs(O);
            wg_fence();
            issue_pv(O, P, vaddr, blk != 0);
            wg_commit();
            wg_wait<0>();
            fence_regs(O); fence_regs(P);
            bar_sync(5 + cw, 128);
          }
          finish_sums();
          pack_o(l0, l1);
          store_o(tile);
        }
      }
    }
  }
  asm volatile("barrier.cluster.wait.aligned;\n" ::: "memory");
}

}

typedef CUresult (*EncodeTiledFn)(CUtensorMap*, CUtensorMapDataType, cuuint32_t, void*, const cuuint64_t*, const cuuint64_t*, const cuuint32_t*,
                                  const cuuint32_t*, CUtensorMapInterleave, CUtensorMapSwizzle, CUtensorMapL2promotion, CUtensorMapFloatOOBfill);

extern "C" void kernel_launch(void* const* d_in, const int* in_sizes, int n_in, void* d_out, int out_size) {
  const int* qk = (const int*)d_in[1];
  const int* qv = (const int*)d_in[2];
  const __nv_bfloat16* ks = (const __nv_bfloat16*)d_in[3];
  const __nv_bfloat16* kz = (const __nv_bfloat16*)d_in[4];
  const __nv_bfloat16* vs = (const __nv_bfloat16*)d_in[5];
  const __nv_bfloat16* vz = (const __nv_bfloat16*)d_in[6];
  __nv_bfloat16* out = (__nv_bfloat16*)d_out;
  static EncodeTiledFn encode = nullptr;
  static int fused = 0;
  static uint8_t* scr = nullptr;
  if (!encode) {
    void* sp = nullptr;
    cudaGetSymbolAddress(&sp, g_scratch);
    scr = (uint8_t*)(((uintptr_t)sp + HEAD_STRIDE - 1) & ~(uintptr_t)(HEAD_STRIDE - 1));
    cudaFuncSetAttribute(attn_kernel, cudaFuncAttributeMaxDynamicSharedMemorySize, SMEM_BYTES);
    {
      cudaLaunchConfig_t cfg = {};
      cfg.gridDim = dim3(NCTAS); cfg.blockDim = dim3(384); cfg.dynamicSmemBytes = SMEM_BYTES;
      cudaLaunchAttribute at[1];
      at[0].id = cudaLaunchAttributeClusterDimension; at[0].val.clusterDim.x = CL; at[0].val.clusterDim.y = 1; at[0].val.clusterDim.z = 1;
      cfg.attrs = at; cfg.numAttrs = 1;
      int nc = 0;
      fused = cudaOccupancyMaxActiveClusters(&nc, attn_kernel, &cfg) == cudaSuccess && nc * CL >= NCTAS;
    }
    void* fn = nullptr;
    cudaDriverEntryPointQueryResult qres;
    cudaGetDriverEntryPoint("cuTensorMapEncodeTiled", &fn, cudaEnableDefault, &qres);
    encode = (EncodeTiledFn)fn;
  }
  CUtensorMap tmq;
  {
    const cuuint64_t dims[2] = {(cuuint64_t)DH, (cuuint64_t)HQ * SQ};
    const cuuint64_t strides[1] = {(cuuint64_t)DH * 2};
    const cuuint32_t box[2] = {64, QROWS};
    const cuuint32_t estr[2] = {1, 1};
    encode(&tmq, CU_TENSOR_MAP_DATA_TYPE_BFLOAT16, 2, d_in[0], dims, strides, box, estr, CU_TENSOR_MAP_INTERLEAVE_NONE, CU_TENSOR_MAP_SWIZZLE_128B,
           CU_TENSOR_MAP_L2_PROMOTION_L2_256B, CU_TENSOR_MAP_FLOAT_OOB_FILL_NONE);
  }
  const DqCtx dq = {qk, qv, ks, kz, vs, vz, scr};
  if (!fused) dequant_kernel<<<(2 * HKV * SKV) / (8 * 4), 256>>>(qk, qv, ks, kz, vs, vz, scr);
  attn_kernel<<<NCTAS, 384, SMEM_BYTES>>>(dq, (const __nv_bfloat16*)d_in[0], out, 0u, fused, tmq);
}
```

```cpp
#include <cuda_runtime.h>
#include <cuda.h>
#include <cuda_bf16.h>
#include <stdint.h>

namespace {

constexpr int HQ = 32, HKV = 4, SQ = 2048, SKV = 2048, DH = 128;
constexpr int BN = 128;
constexpr int NBLK = SKV / BN;
constexpr int TILE_BYTES = BN * DH * 2;
constexpr int HALF_BYTES = TILE_BYTES / 2;
#define NK_STAGES 3
#ifndef NV_STAGES
#define NV_STAGES 3
#endif
constexpr int NK = NK_STAGES, NV = NV_STAGES;
constexpr int TILES_PER_CTA = 4;
#define CL 2
constexpr int NCTAS = 128;
#define QROWS 32
#define QFIRST 2
constexpr int QP = 2 * 128 / QROWS;
constexpr int SLICE = (SKV / SKV) * 32768 / CL;
constexpr int ZS_OFF = 256;
constexpr int SMEM_BYTES = (NK + NV + 1) * TILE_BYTES + 1024 + ZS_OFF + 512;

constexpr size_t PAGE = 2u << 20, HEAD_STRIDE = 2 * PAGE, IMG_OFF = 64u << 10, REGION_BYTES = 1u << 20;
constexpr int SLICES = 32;
constexpr int LINE_FINAL = 2 * NBLK;
__device__ __align__(1024) uint8_t g_scratch[HKV * HEAD_STRIDE + PAGE];
constexpr int NHELP = 4, HBLK = 1, PART_WG = 33 << 10, PART_BYTES = 2 * PART_WG, LINE_PART = 64;
__device__ __align__(1024) uint8_t g_part[128 * PART_BYTES];
__device__ __forceinline__ uint8_t* region(uint8_t* scr, int h, uint32_t par) { return scr + h * HEAD_STRIDE + IMG_OFF + par * REGION_BYTES; }
__device__ __forceinline__ unsigned* cnt_line(uint8_t* reg, int line) {
  const uint64_t a = reinterpret_cast<uint64_t>(reg);
  return reinterpret_cast<unsigned*>((a & ~(uint64_t)(PAGE - 1)) + ((uint32_t)(a >> 18) & 4u) + line * 128);
}

#define TS(e)
#define ST2(k)
#define PR(k)
#define LS(k)

__device__ __forceinline__ uint32_t smem_u32(const void* p) { return (uint32_t)__cvta_generic_to_shared(p); }
__device__ __forceinline__ void wg_fence() { asm volatile("wgmma.fence.sync.aligned;\n" ::: "memory"); }
__device__ __forceinline__ void wg_commit() { asm volatile("wgmma.commit_group.sync.aligned;\n" ::: "memory"); }
template <int N> __device__ __forceinline__ void wg_wait() { asm volatile("wgmma.wait_group.sync.aligned %0;\n" ::"n"(N) : "memory"); }
template <int NR> __device__ __forceinline__ void fence_regs(float (&d)[NR]) {
#pragma unroll
  for (int i = 0; i < NR; i++) asm volatile("" : "+f"(d[i])::"memory");
}
template <int NR> __device__ __forceinline__ void fence_regs(uint32_t (&d)[NR]) {
#pragma unroll
  for (int i = 0; i < NR; i++) asm volatile("" : "+r"(d[i])::"memory");
}
__device__ __forceinline__ void bar_sync(int id, int n) { asm volatile("bar.sync %0, %1;\n" ::"r"(id), "r"(n) : "memory"); }
__device__ __forceinline__ void bar_arrive(int id, int n) { asm volatile("bar.arrive %0, %1;\n" ::"r"(id), "r"(n) : "memory"); }
__device__ __forceinline__ void bar_sync_sel(uint32_t second) {
  asm volatile("{\n.reg .pred p;\nsetp.ne.u32 p, %0, 0;\n@!p bar.sync 1, 256;\n@p bar.sync 2, 256;\n}\n" ::"r"(second) : "memory");
}
__device__ __forceinline__ void bar_arrive_sel(uint32_t second) {
  asm volatile("{\n.reg .pred p;\nsetp.ne.u32 p, %0, 0;\n@!p bar.arrive 1, 256;\n@p bar.arrive 2, 256;\n}\n" ::"r"(second) : "memory");
}
__device__ __forceinline__ void mbar_init(uint32_t bar, uint32_t count) {
  asm volatile("mbarrier.init.shared::cta.b64 [%0], %1;\n" ::"r"(bar), "r"(count) : "memory");
}
__device__ __forceinline__ void mbar_expect_tx(uint32_t bar, uint32_t bytes) {
  asm volatile("mbarrier.arrive.expect_tx.shared::cta.b64 _, [%0], %1;\n" ::"r"(bar), "r"(bytes) : "memory");
}
__device__ __forceinline__ void mbar_wait(uint32_t bar, uint32_t parity) {
  asm volatile(
      "{\n.reg .pred p;\n"
      "WAIT_LOOP:\n"
      "mbarrier.try_wait.parity.shared::cta.b64 p, [%0], %1;\n"
      "@p bra WAIT_DONE;\n"
      "bra WAIT_LOOP;\n"
      "WAIT_DONE:\n}\n" ::"r"(bar), "r"(parity) : "memory");
}
__device__ __forceinline__ uint32_t mbar_test(uint32_t bar, uint32_t parity) {
  uint32_t ok;
  asm volatile("{\n.reg .pred p;\nmbarrier.test_wait.parity.shared::cta.b64 p, [%1], %2;\nselp.u32 %0, 1, 0, p;\n}\n" : "=r"(ok) : "r"(bar), "r"(parity) : "memory");
  return ok;
}
__device__ __forceinline__ void mma_16816(float& c0, float& c1, float& c2, float& c3, uint32_t a0, uint32_t a1, uint32_t a2, uint32_t a3, uint32_t b0, uint32_t b1) {
  asm volatile("mma.sync.aligned.m16n8k16.row.col.f32.bf16.bf16.f32 {%0, %1, %2, %3}, {%4, %5, %6, %7}, {%8, %9}, {%0, %1, %2, %3};\n"
               : "+f"(c0), "+f"(c1), "+f"(c2), "+f"(c3) : "r"(a0), "r"(a1), "r"(a2), "r"(a3), "r"(b0), "r"(b1));
}
__device__ __forceinline__ float rcp_fast(float x) {
  float y;
  asm("rcp.approx.ftz.f32 %0, %1;\n" : "=f"(y) : "f"(x));
  return y;
}
__device__ __forceinline__ void mbar_arrive_local(uint32_t bar) {
  asm volatile("mbarrier.arrive.shared::cta.b64 _, [%0];\n" ::"r"(bar) : "memory");
}
__device__ __forceinline__ void mbar_arrive_cluster(uint32_t bar, uint32_t cta) {
  asm volatile(
      "{\n.reg .b32 ra;\n"
      "mapa.shared::cluster.u32 ra, %0, %1;\n"
      "mbarrier.arrive.shared::cluster.b64 _, [ra];\n}\n" ::"r"(bar), "r"(cta) : "memory");
}
__device__ __forceinline__ void bulk_load_mc(uint32_t dst, const void* src, uint32_t bytes, uint32_t bar, uint16_t mask) {
  asm volatile(
      "cp.async.bulk.shared::cluster.global.mbarrier::complete_tx::bytes.multicast::cluster [%0], [%1], %2, [%3], %4;\n" ::"r"(dst),
      "l"(src), "r"(bytes), "r"(bar), "h"(mask)
      : "memory");
}
__device__ __forceinline__ void bulk_load(uint32_t dst, const void* src, uint32_t bytes, uint32_t bar) {
  asm volatile("cp.async.bulk.shared::cluster.global.mbarrier::complete_tx::bytes [%0], [%1], %2, [%3];\n" ::"r"(dst), "l"(src),
               "r"(bytes), "r"(bar)
               : "memory");
}
__device__ __forceinline__ void tma_load_2d(uint32_t dst, const void* tmap, int c0, int c1, uint32_t bar) {
  asm volatile("cp.async.bulk.tensor.2d.shared::cluster.global.mbarrier::complete_tx::bytes [%0], [%1, {%3, %4}], [%2];\n" ::"r"(dst), "l"(tmap),
               "r"(bar), "r"(c0), "r"(c1)
               : "memory");
}
__device__ __forceinline__ void ldsm_x4(uint32_t& r0, uint32_t& r1, uint32_t& r2, uint32_t& r3, uint32_t addr) {
  asm volatile("ldmatrix.sync.aligned.m8n8.x4.shared.b16 {%0, %1, %2, %3}, [%4];\n" : "=r"(r0), "=r"(r1), "=r"(r2), "=r"(r3) : "r"(addr) : "memory");
}
__device__ __forceinline__ bool wg_any(bool p, int id) {
  uint32_t r;
  asm volatile("{\n.reg .pred p, q;\nsetp.ne.u32 p, %1, 0;\nbarrier.cta.red.or.aligned.pred q, %2, 128, p;\nselp.u32 %0, 1, 0, q;\n}\n"
               : "=r"(r) : "r"((uint32_t)p), "r"(id) : "memory");
  return r != 0;
}
__device__ __forceinline__ float ex2(float x) {
  float y;
  asm("ex2.approx.ftz.f32 %0, %1;\n" : "=f"(y) : "f"(x));
  return y;
}
__device__ __forceinline__ uint32_t pack_bf16(float lo, float hi) {
  uint32_t r;
  asm("cvt.rn.bf16x2.f32 %0, %1, %2;\n" : "=r"(r) : "f"(hi), "f"(lo));
  return r;
}
__device__ __forceinline__ uint64_t make_desc(uint32_t addr, uint32_t lbo, uint32_t sbo) {
  return (uint64_t)((addr & 0x3FFFF) >> 4) | ((uint64_t)(lbo >> 4) << 16) | ((uint64_t)(sbo >> 4) << 32) | (1ull << 62);
}

__device__ __forceinline__ void wgmma_rs_kmaj(float (&d)[64], uint32_t a0, uint32_t a1, uint32_t a2, uint32_t a3, uint64_t descB, int scaleD) {
  asm volatile("{\n.reg .pred p;\nsetp.ne.b32 p, %69, 0;\n"
    "wgmma.mma_async.sync.aligned.m64n128k16.f32.bf16.bf16 "
    "{%0, %1, %2, %3, %4, %5, %6, %7, %8, %9, %10, %11, %12, %13, %14, %15, "
    "%16, %17, %18, %19, %20, %21, %22, %23, %24, %25, %26, %27, %28, %29, %30, %31, "
    "%32, %33, %34, %35, %36, %37, %38, %39, %40, %41, %42, %43, %44, %45, %46, %47, "
    "%48, %49, %50, %51, %52, %53, %54, %55, %56, %57, %58, %59, %60, %61, %62, %63}, "
    "{%64, %65, %66, %67}, %68, p, 1, 1, 0;\n}\n"
    : "+f"(d[0]), "+f"(d[1]), "+f"(d[2]), "+f"(d[3]), "+f"(d[4]), "+f"(d[5]), "+f"(d[6]), "+f"(d[7]),
      "+f"(d[8]), "+f"(d[9]), "+f"(d[10]), "+f"(d[11]), "+f"(d[12]), "+f"(d[13]), "+f"(d[14]), "+f"(d[15]),
      "+f"(d[16]), "+f"(d[17]), "+f"(d[18]), "+f"(d[19]), "+f"(d[20]), "+f"(d[21]), "+f"(d[22]), "+f"(d[23]),
      "+f"(d[24]), "+f"(d[25]), "+f"(d[26]), "+f"(d[27]), "+f"(d[28]), "+f"(d[29]), "+f"(d[30]), "+f"(d[31]),
      "+f"(d[32]), "+f"(d[33]), "+f"(d[34]), "+f"(d[35]), "+f"(d[36]), "+f"(d[37]), "+f"(d[38]), "+f"(d[39]),
      "+f"(d[40]), "+f"(d[41]), "+f"(d[42]), "+f"(d[43]), "+f"(d[44]), "+f"(d[45]), "+f"(d[46]), "+f"(d[47]),
      "+f"(d[48]), "+f"(d[49]), "+f"(d[50]), "+f"(d[51]), "+f"(d[52]), "+f"(d[53]), "+f"(d[54]), "+f"(d[55]),
      "+f"(d[56]), "+f"(d[57]), "+f"(d[58]), "+f"(d[59]), "+f"(d[60]), "+f"(d[61]), "+f"(d[62]), "+f"(d[63])
    : "r"(a0), "r"(a1), "r"(a2), "r"(a3), "l"(descB), "r"(scaleD));
}

__device__ __forceinline__ void wgmma_ss_kmaj(float (&d)[64], uint64_t descA, uint64_t descB, int scaleD) {
  asm volatile("{\n.reg .pred p;\nsetp.ne.b32 p, %66, 0;\n"
    "wgmma.mma_async.sync.aligned.m64n128k16.f32.bf16.bf16 "
    "{%0, %1, %2, %3, %4, %5, %6, %7, %8, %9, %10, %11, %12, %13, %14, %15, "
    "%16, %17, %18, %19, %20, %21, %22, %23, %24, %25, %26, %27, %28, %29, %30, %31, "
    "%32, %33, %34, %35, %36, %37, %38, %39, %40, %41, %42, %43, %44, %45, %46, %47, "
    "%48, %49, %50, %51, %52, %53, %54, %55, %56, %57, %58, %59, %60, %61, %62, %63}, "
    "%64, %65, p, 1, 1, 0, 0;\n}\n"
    : "+f"(d[0]), "+f"(d[1]), "+f"(d[2]), "+f"(d[3]), "+f"(d[4]), "+f"(d[5]), "+f"(d[6]), "+f"(d[7]),
      "+f"(d[8]), "+f"(d[9]), "+f"(d[10]), "+f"(d[11]), "+f"(d[12]), "+f"(d[13]), "+f"(d[14]), "+f"(d[15]),
      "+f"(d[16]), "+f"(d[17]), "+f"(d[18]), "+f"(d[19]), "+f"(d[20]), "+f"(d[21]), "+f"(d[22]), "+f"(d[23]),
      "+f"(d[24]), "+f"(d[25]), "+f"(d[26]), "+f"(d[27]), "+f"(d[28]), "+f"(d[29]), "+f"(d[30]), "+f"(d[31]),
      "+f"(d[32]), "+f"(d[33]), "+f"(d[34]), "+f"(d[35]), "+f"(d[36]), "+f"(d[37]), "+f"(d[38]), "+f"(d[39]),
      "+f"(d[40]), "+f"(d[41]), "+f"(d[42]), "+f"(d[43]), "+f"(d[44]), "+f"(d[45]), "+f"(d[46]), "+f"(d[47]),
      "+f"(d[48]), "+f"(d[49]), "+f"(d[50]), "+f"(d[51]), "+f"(d[52]), "+f"(d[53]), "+f"(d[54]), "+f"(d[55]),
      "+f"(d[56]), "+f"(d[57]), "+f"(d[58]), "+f"(d[59]), "+f"(d[60]), "+f"(d[61]), "+f"(d[62]), "+f"(d[63])
    : "l"(descA), "l"(descB), "r"(scaleD));
}

__device__ __forceinline__ void wgmma_rs_nmaj(float (&d)[64], uint32_t a0, uint32_t a1, uint32_t a2, uint32_t a3, uint64_t descB, int scaleD) {
  asm volatile("{\n.reg .pred p;\nsetp.ne.b32 p, %69, 0;\n"
    "wgmma.mma_async.sync.aligned.m64n128k16.f32.bf16.bf16 "
    "{%0, %1, %2, %3, %4, %5, %6, %7, %8, %9, %10, %11, %12, %13, %14, %15, "
    "%16, %17, %18, %19, %20, %21, %22, %23, %24, %25, %26, %27, %28, %29, %30, %31, "
    "%32, %33, %34, %35, %36, %37, %38, %39, %40, %41, %42, %43, %44, %45, %46, %47, "
    "%48, %49, %50, %51, %52, %53, %54, %55, %56, %57, %58, %59, %60, %61, %62, %63}, "
    "{%64, %65, %66, %67}, %68, p, 1, 1, 1;\n}\n"
    : "+f"(d[0]), "+f"(d[1]), "+f"(d[2]), "+f"(d[3]), "+f"(d[4]), "+f"(d[5]), "+f"(d[6]), "+f"(d[7]),
      "+f"(d[8]), "+f"(d[9]), "+f"(d[10]), "+f"(d[11]), "+f"(d[12]), "+f"(d[13]), "+f"(d[14]), "+f"(d[15]),
      "+f"(d[16]), "+f"(d[17]), "+f"(d[18]), "+f"(d[19]), "+f"(d[20]), "+f"(d[21]), "+f"(d[22]), "+f"(d[23]),
      "+f"(d[24]), "+f"(d[25]), "+f"(d[26]), "+f"(d[27]), "+f"(d[28]), "+f"(d[29]), "+f"(d[30]), "+f"(d[31]),
      "+f"(d[32]), "+f"(d[33]), "+f"(d[34]), "+f"(d[35]), "+f"(d[36]), "+f"(d[37]), "+f"(d[38]), "+f"(d[39]),
      "+f"(d[40]), "+f"(d[41]), "+f"(d[42]), "+f"(d[43]), "+f"(d[44]), "+f"(d[45]), "+f"(d[46]), "+f"(d[47]),
      "+f"(d[48]), "+f"(d[49]), "+f"(d[50]), "+f"(d[51]), "+f"(d[52]), "+f"(d[53]), "+f"(d[54]), "+f"(d[55]),
      "+f"(d[56]), "+f"(d[57]), "+f"(d[58]), "+f"(d[59]), "+f"(d[60]), "+f"(d[61]), "+f"(d[62]), "+f"(d[63])
    : "r"(a0), "r"(a1), "r"(a2), "r"(a3), "l"(descB), "r"(scaleD));
}

struct DqCtx { const int* qk; const int* qv; const __nv_bfloat16 *ks, *kz, *vs, *vz; uint8_t* scr; };
__device__ __forceinline__ float bf_lo(uint32_t u) { return __uint_as_float(u << 16); }
__device__ __forceinline__ float bf_hi(uint32_t u) { return __uint_as_float(u & 0xffff0000u); }
__device__ __forceinline__ float bf_round(float x) { return __bfloat162float(__float2bfloat16_rn(x)); }
__device__ __forceinline__ uint32_t dq_pair_small(uint32_t a, uint32_t b, uint32_t z2, uint32_t s2) {
  uint32_t r;
  asm("{\n.reg .b32 y, d;\n"
      "mul.rn.bf16x2 y, %1, %4;\n"
      "fma.rn.bf16x2 d, y, %5, %2;\n"
      "mul.rn.bf16x2 %0, d, %3;\n}\n" : "=r"(r) : "r"(a + (b << 16)), "r"(z2), "r"(s2), "r"(0x7f007f00u), "r"(0xc280c280u));
  return r;
}
template <bool HI> __device__ __forceinline__ uint32_t dq_pair_small1(uint32_t a, uint32_t b, uint32_t z, uint32_t s) {
  uint32_t r;
  if (HI)
    asm("{\n.reg .b32 y, d, zb, sb;\n.reg .b16 l, h;\n"
        "mov.b32 {l, h}, %2;\nmov.b32 zb, {h, h};\nmov.b32 {l, h}, %3;\nmov.b32 sb, {h, h};\n"
        "mul.rn.bf16x2 y, %1, %4;\n"
        "fma.rn.bf16x2 d, y, %5, zb;\n"
        "mul.rn.bf16x2 %0, d, sb;\n}\n" : "=r"(r) : "r"(a + (b << 16)), "r"(z), "r"(s), "r"(0x7f007f00u), "r"(0xc280c280u));
  else
    asm("{\n.reg .b32 y, d, zb, sb;\n.reg .b16 l, h;\n"
        "mov.b32 {l, h}, %2;\nmov.b32 zb, {l, l};\nmov.b32 {l, h}, %3;\nmov.b32 sb, {l, l};\n"
        "mul.rn.bf16x2 y, %1, %4;\n"
        "fma.rn.bf16x2 d, y, %5, zb;\n"
        "mul.rn.bf16x2 %0, d, sb;\n}\n" : "=r"(r) : "r"(a + (b << 16)), "r"(z), "r"(s), "r"(0x7f007f00u), "r"(0xc280c280u));
  return r;
}
__device__ __forceinline__ uint32_t dq_pair_any(int a, int b, uint32_t z2, uint32_t s2) {
  return pack_bf16(bf_round(bf_round((float)a) - bf_lo(z2)) * bf_lo(s2), bf_round(bf_round((float)b) - bf_hi(z2)) * bf_hi(s2));
}
constexpr float SCALE_LOG2 = 0.08838834764831845f * 1.4426950408889634f;
template <bool NEG = false> __device__ __forceinline__ uint32_t scale_key(uint32_t k2) {
  uint32_t r;
  asm("{\n.reg .b32 t;\n"
      "mul.rn.bf16x2 t, %1, %2;\n"
      "fma.rn.bf16x2 %0, %1, %3, t;\n}\n" : "=r"(r) : "r"(k2), "r"(NEG ? 0x39d839d8u : 0xb9d8b9d8u), "r"(NEG ? 0xbe03be03u : 0x3e033e03u));
  return r;
}
struct DqLane {
  uint32_t srcK, srcV, dst;
  int rr0;
  __device__ __forceinline__ DqLane(int cta, int lane) {
    const int j = lane >> 1;
    rr0 = ((cta >> 2) & 7) * 16 + (cta & 3) * 2;
    srcK = (rr0 * DH + lane * 4) * 4;
    srcV = (rr0 * DH + 32 * (j >> 2) + 2 * (j & 3) + 16 * (lane & 1)) * 4;
    dst = (lane >> 4) * HALF_BYTES + rr0 * 128 + (((j ^ rr0) & 7) << 4) + (lane & 1) * 8;
  }
};
template <int OFF> __device__ __forceinline__ void st_img(uint64_t addr, uint32_t a, uint32_t b) {
  asm volatile("st.relaxed.gpu.global.v2.b32 [%0+%3], {%1, %2};\n" ::"l"(addr), "r"(a), "r"(b), "n"(OFF) : "memory");
}
__device__ __forceinline__ void wait_final(uint8_t* reg) {
  unsigned v, n = 0;
  do {
    asm volatile("ld.acquire.gpu.global.u32 %0, [%1];\n" : "=r"(v) : "l"(cnt_line(reg, LINE_FINAL)) : "memory");
    if (++n > (1u << 24)) __trap();
  } while (v < 4 * SLICES);
  asm volatile("fence.proxy.async.global;\n" ::: "memory");
}
__device__ __forceinline__ void dq_rows_any(const DqCtx& d, const DqLane& L, uint8_t* reg, int h, int t, int lane) {
  const int j = lane >> 1;
  const bool isV = t & 1;
  const int blk = h * NBLK + (t >> 1);
  const int c0 = isV ? 32 * (j >> 2) + 2 * (j & 3) + 16 * (lane & 1) : lane * 4, c1 = isV ? c0 + 8 : c0 + 2;
  const uint64_t dA = reinterpret_cast<uint64_t>(reg) + (uint32_t)(t * TILE_BYTES + L.dst);
#pragma unroll 1
  for (int i = 0; i < 4; i++) {
    const int tok = blk * BN + L.rr0 + (i & 1) + (i >> 1) * 8;
    const int* src = (isV ? d.qv : d.qk) + (size_t)tok * DH;
    uint32_t za, zb, sa, sb;
    if (isV) {
      za = zb = (uint32_t)__bfloat16_as_ushort(d.vz[tok]) * 0x10001u; sa = sb = (uint32_t)__bfloat16_as_ushort(d.vs[tok]) * 0x10001u;
    } else {
      const uint32_t* zp = reinterpret_cast<const uint32_t*>(d.kz + blk * DH + lane * 4);
      const uint32_t* sp = reinterpret_cast<const uint32_t*>(d.ks + blk * DH + lane * 4);
      za = zp[0]; zb = zp[1]; sa = sp[0]; sb = sp[1];
    }
    uint32_t w0 = dq_pair_any(src[c0], src[c0 + 1], za, sa), w1 = dq_pair_any(src[c1], src[c1 + 1], zb, sb);
    if (!isV) { w0 = scale_key(w0); w1 = scale_key(w1); } else { w0 ^= 0x80008000u; w1 ^= 0x80008000u; }
    st_img<0>((dA ^ ((i & 1) * 0x90)) + (i >> 1) * 1024, w0, w1);
  }
}
struct DqTask {
  uint32_t x[4][4];
  uint32_t z[2], s[2];
  template <bool isV> __device__ __forceinline__ void load(const DqCtx& d, const DqLane& L, int blk, int lane) {
    if (isV) {
      const uint8_t* src = reinterpret_cast<const uint8_t*>(d.qv) + (size_t)(uint32_t)(blk * (BN * DH * 4) + L.srcV);
#pragma unroll
      for (int i = 0; i < 4; i++) {
        const uint8_t* p = src + ((i & 1) + (i >> 1) * 8) * (DH * 4);
        const int2 a = __ldcs(reinterpret_cast<const int2*>(p)), b = __ldcs(reinterpret_cast<const int2*>(p + 32));
        x[i][0] = a.x; x[i][1] = a.y; x[i][2] = b.x; x[i][3] = b.y;
      }
      const uint32_t* zp = reinterpret_cast<const uint32_t*>(d.vz + blk * BN + L.rr0);
      const uint32_t* sp = reinterpret_cast<const uint32_t*>(d.vs + blk * BN + L.rr0);
      z[0] = __ldg(zp); z[1] = __ldg(zp + 4); s[0] = __ldg(sp); s[1] = __ldg(sp + 4);
    } else {
      const uint8_t* src = reinterpret_cast<const uint8_t*>(d.qk) + (size_t)(uint32_t)(blk * (BN * DH * 4) + L.srcK);
#pragma unroll
      for (int i = 0; i < 4; i++) {
        const int4 a = __ldcs(reinterpret_cast<const int4*>(src + ((i & 1) + (i >> 1) * 8) * (DH * 4)));
        x[i][0] = a.x; x[i][1] = a.y; x[i][2] = a.z; x[i][3] = a.w;
      }
      const uint32_t o = blk * (DH * 2) + lane * 8;
      const uint2 zz = __ldg(reinterpret_cast<const uint2*>(reinterpret_cast<const uint8_t*>(d.kz) + o));
      const uint2 ss = __ldg(reinterpret_cast<const uint2*>(reinterpret_cast<const uint8_t*>(d.ks) + o));
      z[0] = zz.x; z[1] = zz.y; s[0] = ss.x; s[1] = ss.y;
    }
  }
  template <bool isV> __device__ __forceinline__ bool store(const DqLane& L, uint8_t* img) const {
    uint32_t any = 0;
#pragma unroll
    for (int i = 0; i < 4; i++) any |= x[i][0] | x[i][1] | x[i][2] | x[i][3];
    if (__builtin_expect(__any_sync(0xffffffffu, any >= 256u), 0)) return true;
    uint64_t dA = reinterpret_cast<uint64_t>(img) + L.dst;
    if (isV) {
      st_img<0>(dA, dq_pair_small1<false>(x[0][0], x[0][1], z[0], s[0]), dq_pair_small1<false>(x[0][2], x[0][3], z[0], s[0]));
      st_img<1024>(dA, dq_pair_small1<false>(x[2][0], x[2][1], z[1], s[1]), dq_pair_small1<false>(x[2][2], x[2][3], z[1], s[1]));
      asm volatile("xor.b64 %0, %0, 0x90;\n" : "+l"(dA));
      st_img<0>(dA, dq_pair_small1<true>(x[1][0], x[1][1], z[0], s[0]), dq_pair_small1<true>(x[1][2], x[1][3], z[0], s[0]));
      st_img<1024>(dA, dq_pair_small1<true>(x[3][0], x[3][1], z[1], s[1]), dq_pair_small1<true>(x[3][2], x[3][3], z[1], s[1]));
    } else {
      st_img<0>(dA, scale_key<true>(dq_pair_small(x[0][0], x[0][1], z[0], s[0])), scale_key<true>(dq_pair_small(x[0][2], x[0][3], z[1], s[1])));
      st_img<1024>(dA, scale_key<true>(dq_pair_small(x[2][0], x[2][1], z[0], s[0])), scale_key<true>(dq_pair_small(x[2][2], x[2][3], z[1], s[1])));
      asm volatile("xor.b64 %0, %0, 0x90;\n" : "+l"(dA));
      st_img<0>(dA, scale_key<true>(dq_pair_small(x[1][0], x[1][1], z[0], s[0])), scale_key<true>(dq_pair_small(x[1][2], x[1][3], z[1], s[1])));
      st_img<1024>(dA, scale_key<true>(dq_pair_small(x[3][0], x[3][1], z[0], s[0])), scale_key<true>(dq_pair_small(x[3][2], x[3][3], z[1], s[1])));
    }
    return false;
  }
  static __device__ __forceinline__ int tile_of(int u) { return u < 2 * NBLK - 2 ? ((u & 1) ? u : u + 2) : (u == 2 * NBLK - 2 ? u + 1 : 0); }
  __device__ __forceinline__ void load_tile(const DqCtx& d, const DqLane& L, int h, int t, int lane) {
    if (t & 1) load<true>(d, L, h * NBLK + (t >> 1), lane); else load<false>(d, L, h * NBLK + (t >> 1), lane);
  }
  __device__ __forceinline__ bool store_tile(const DqLane& L, uint8_t* reg, int t, int lane) const {
    const bool left = (t & 1) ? store<true>(L, reg + t * TILE_BYTES) : store<false>(L, reg + t * TILE_BYTES);
    if (!left && lane == 0) asm volatile("red.relaxed.gpu.global.add.u32 [%0], 1;\n" ::"l"(cnt_line(reg, t)) : "memory");
    return left;
  }
};

__global__ void __launch_bounds__(256) dequant_kernel(const int* __restrict__ qk, const int* __restrict__ qv,
                                                      const __nv_bfloat16* __restrict__ ks, const __nv_bfloat16* __restrict__ kz,
                                                      const __nv_bfloat16* __restrict__ vs, const __nv_bfloat16* __restrict__ vz, uint8_t* scr) {
  constexpr int ROWS_PER_WARP = 4;
  const int lane = threadIdx.x & 31;
  const int warp = blockIdx.x * 8 + (threadIdx.x >> 5);
  const int row0 = warp * ROWS_PER_WARP;
  const bool isV = row0 >= HKV * SKV;
  const int r0 = isV ? row0 - HKV * SKV : row0;
  const int* src = (isV ? qv : qk) + (size_t)r0 * DH + lane * 4;
  int4 x[ROWS_PER_WARP];
#pragma unroll
  for (int i = 0; i < ROWS_PER_WARP; i++) x[i] = __ldcs(reinterpret_cast<const int4*>(src + i * DH));
  float z[4], s[4];
  if (!isV) {
    const int g = r0 / BN;
    const uint2 zz = *reinterpret_cast<const uint2*>(kz + (size_t)g * DH + lane * 4);
    const uint2 ss = *reinterpret_cast<const uint2*>(ks + (size_t)g * DH + lane * 4);
    z[0] = __uint_as_float(zz.x << 16); z[1] = __uint_as_float(zz.x & 0xffff0000u);
    z[2] = __uint_as_float(zz.y << 16); z[3] = __uint_as_float(zz.y & 0xffff0000u);
    s[0] = __uint_as_float(ss.x << 16); s[1] = __uint_as_float(ss.x & 0xffff0000u);
    s[2] = __uint_as_float(ss.y << 16); s[3] = __uint_as_float(ss.y & 0xffff0000u);
  }
  uint8_t* img = region(scr, r0 / SKV, 0) + (size_t)(2 * ((r0 / BN) & (NBLK - 1)) + isV) * TILE_BYTES;
  const int J = lane >> 3, c = (lane & 7) >> 1, sb = lane & 1;
  const int j = 4 * J + 2 * sb + (c & 1);
  const int half = j >> 3, ch = j & 7;
#pragma unroll
  for (int i = 0; i < ROWS_PER_WARP; i++) {
    const int r = r0 + i;
    if (isV) {
      const float zv = __bfloat162float(vz[r]), sv = __bfloat162float(vs[r]);
#pragma unroll
      for (int e = 0; e < 4; e++) { z[e] = zv; s[e] = sv; }
    }
    const int xi[4] = {x[i].x, x[i].y, x[i].z, x[i].w};
    float o[4];
#pragma unroll
    for (int e = 0; e < 4; e++) {
      const float qf = __bfloat162float(__float2bfloat16_rn((float)xi[e]));
      const float df = __bfloat162float(__float2bfloat16_rn(qf - z[e]));
      o[e] = df * s[e];
    }
    const uint32_t p0 = pack_bf16(o[0], o[1]), p1 = pack_bf16(o[2], o[3]);
    const int rr = r & (BN - 1);
    uint2 w;
    if (isV) {
      const uint32_t send = (c & 1) ? p0 : p1;
      const uint32_t recv = __shfl_xor_sync(0xffffffffu, send, 2);
      if (c & 1) { w.x = recv; w.y = p1; } else { w.x = p0; w.y = recv; }
      w.x ^= 0x80008000u; w.y ^= 0x80008000u;
      *reinterpret_cast<uint2*>(img + half * HALF_BYTES + rr * 128 + ((ch ^ (rr & 7)) << 4) + (c >> 1) * 8) = w;
    } else {
      w.x = scale_key(p0); w.y = scale_key(p1);
      *reinterpret_cast<uint2*>(img + (lane >> 4) * HALF_BYTES + rr * 128 + ((((lane >> 1) & 7) ^ (rr & 7)) << 4) + (lane & 1) * 8) = w;
    }
  }
}

#define SPLIT 5
#define DEPD 2
constexpr float SUM_LO = 5.9604644775390625e-8f, SUM_HI = 1099511627776.0f;

__device__ __forceinline__ void issue_qk(float (&S)[64], const uint32_t (&Q)[32], uint32_t kaddr) {
  const uint64_t d0 = make_desc(kaddr, 16, 1024);
#pragma unroll
  for (int k = 0; k < 8; k++)
    wgmma_rs_kmaj(S, Q[4 * k], Q[4 * k + 1], Q[4 * k + 2], Q[4 * k + 3], d0 + (uint64_t)(((k & 3) * 32 + (k >> 2) * HALF_BYTES) >> 4), k != 0);
}
__device__ __forceinline__ void issue_qk_ss(float (&S)[64], uint32_t qaddr, uint32_t kaddr) {
  const uint64_t a0 = make_desc(qaddr, 16, 1024), d0 = make_desc(kaddr, 16, 1024);
#pragma unroll
  for (int k = 0; k < 8; k++) {
    const uint64_t off = (uint64_t)(((k & 3) * 32 + (k >> 2) * HALF_BYTES) >> 4);
    wgmma_ss_kmaj(S, a0 + off, d0 + off, k != 0);
  }
}
__device__ __forceinline__ void issue_pv(float (&O)[64], const uint32_t (&P)[32], uint32_t vaddr, int acc) {
  const uint64_t d0 = make_desc(vaddr, HALF_BYTES, 1024);
#pragma unroll
  for (int k = 0; k < 8; k++)
    wgmma_rs_nmaj(O, P[4 * k], P[4 * k + 1], P[4 * k + 2], P[4 * k + 3], d0 + (uint64_t)((k * 2048) >> 4), (k != 0) | acc);
}
__device__ __forceinline__ float tie(float a, float b, uint32_t z) {
  uint32_t r;
  asm("lop3.b32 %0, %1, %2, %3, 0xF8;\n" : "=r"(r) : "r"(__float_as_uint(a)), "r"(__float_as_uint(b)), "r"(z));
  return __uint_as_float(r);
}

__device__ __forceinline__ uint32_t tieu(uint32_t a, float b, uint32_t z) {
  uint32_t r;
  asm("lop3.b32 %0, %1, %2, %3, 0xF8;\n" : "=r"(r) : "r"(a), "r"(__float_as_uint(b)), "r"(z));
  return r;
}

#define BAR_SYNC_MINE bar_sync(my_bar, 256)
#define BAR_ARRIVE_OTHER bar_arrive(other_bar, 256)
#define LDSM_POS 0
template <bool B> struct BoolC { static constexpr bool value = B; };
template <int N> struct IntC { static constexpr int value = N; };
#define POLL0 3000
#define POLL0_GAP 400
#define RAWN 2
#define RAWG 8

#define QWIN 3
#define QWIN1 QWIN
#define LL_GAP 0
#define LL_T0 1000
#define LL_HINT SLICES
#define LL_CLEAR 20
#define Q_DELAY 0
#define Q_DELAY1 2200
#define NPRE 1
#define POLLW 4
#define POLL_GAP 0
#define EARLY_FROM 3
#define B_DELAY 3600
#define PDEPTH 1
#define H_DELAY 5000
#define H_EARLY(cw) (cw)
#define H_GAP 1500
__device__ __forceinline__ void helper(const DqCtx& dq, const CUtensorMap* tmq0, uint32_t sbase, int h) {
  const uint32_t t_start = clock();
  const uint32_t sK = sbase, sV = sbase + NK * TILE_BYTES, bars = sbase + (NK + NV + 1) * TILE_BYTES;
  const uint32_t fullKV = bars, fullQ = bars + 8, sflag = bars + 80, freeb = bars + 96;
  const uint32_t stage = sV + TILE_BYTES, done = stage + 2 * PART_WG;
  const int warp = __shfl_sync(0xffffffffu, (int)(threadIdx.x >> 5), 0);
  const int lane = threadIdx.x & 31;
  unsigned* const lines = cnt_line(region(dq.scr, h, 0), 0);
  if (threadIdx.x == 0) {
    mbar_init(fullKV, 1);
    for (int i = 0; i < 4; i++) mbar_init(fullQ + 8 * i, 1);
    mbar_init(freeb, 1); mbar_init(freeb + 8, 1);
    const unsigned epoch = *reinterpret_cast<const volatile unsigned*>(lines + 3 * 32 + 2);
    asm volatile("st.shared.u32 [%0], %1;\n" ::"r"(sflag), "r"(epoch) : "memory");
    asm volatile("fence.proxy.async.shared::cta;\n" ::: "memory");
  }
  if (threadIdx.x >= 128 && threadIdx.x < 128 + 2 * SLICES) mbar_init(done + 8 * (threadIdx.x - 128), 4);
  __syncthreads();
  uint32_t epoch;
  asm volatile("ld.shared.u32 %0, [%1];\n" : "=r"(epoch) : "r"(sflag) : "memory");
  if (warp < 4) {
    asm volatile("setmaxnreg.dec.sync.aligned.u32 40;\n");
    while ((uint32_t)clock() - t_start < H_DELAY) __nanosleep(100);
    if (warp == 0) {
      uint8_t* const reg = region(dq.scr, h, epoch & 1);
      if (epoch == 0) wait_final(reg);
      else {
        unsigned v, n = 0;
        do {
          asm volatile("ld.relaxed.gpu.global.u32 %0, [%1];\n" : "=r"(v) : "l"(cnt_line(reg, 2 * HBLK + (lane & 1))) : "memory");
          if (++n > (1u << 24)) __trap();
        } while (!__all_sync(0xffffffffu, v >= LL_HINT));
        const uint32_t t0 = clock();
        while ((uint32_t)clock() - t0 < H_GAP) __nanosleep(100);
      }
      if (lane == 0) {
        mbar_expect_tx(fullKV, 2 * TILE_BYTES);
        bulk_load(sK, reg + (2 * HBLK) * TILE_BYTES, TILE_BYTES, fullKV);
        bulk_load(sV, reg + (2 * HBLK + 1) * TILE_BYTES, TILE_BYTES, fullKV);
      }
    }
    if (lane == 0 && warp < 2) {
#pragma unroll 1
      for (int j = 0; j < SLICES; j++) {
        mbar_wait(done + 8 * (warp * SLICES + j), 0);
        asm volatile("cp.async.bulk.global.shared::cta.bulk_group [%0], [%1], %2;\n" ::"l"(g_part + (size_t)(h * SLICES + j) * PART_BYTES + warp * PART_WG),
                     "r"(stage + warp * PART_WG), "r"(TILE_BYTES + 256) : "memory");
        asm volatile("cp.async.bulk.commit_group;\n" ::: "memory");
        asm volatile("cp.async.bulk.wait_group.read 0;\n" ::: "memory");
        mbar_arrive_local(freeb + 8 * warp);
        asm volatile("cp.async.bulk.wait_group 0;\n" ::: "memory");
        asm volatile("fence.proxy.async.global;\n" ::: "memory");
        asm volatile("fence.acq_rel.gpu;\n" ::: "memory");
        asm volatile("st.relaxed.gpu.global.u32 [%0], %1;\n" ::"l"(lines + (LINE_PART + j) * 32 + warp), "r"(epoch + 1) : "memory");
      }
    }
  } else {
    asm volatile("setmaxnreg.inc.sync.aligned.u32 232;\n");
    while ((uint32_t)clock() - t_start < H_DELAY) __nanosleep(100);
    const int cw = (warp >> 2) - 1, wq = warp & 3, tid = threadIdx.x & 127;
    const uint32_t qbuf = sK + TILE_BYTES + cw * TILE_BYTES;
    const uint32_t qaddr = qbuf + (wq * 16 + (lane & 15)) * 128 + ((((lane >> 4) ^ lane) & 7) << 4);
    const int row0 = h * SLICES * (TILES_PER_CTA * 128) + (TILES_PER_CTA - 1) * 128 + cw * 64;
    auto load_q = [&](int j) {
      const uint32_t bar = fullQ + 8 * (cw * 2 + (j & 1)), dst = qbuf + (j & 1) * HALF_BYTES;
      mbar_expect_tx(bar, HALF_BYTES);
      tma_load_2d(dst, tmq0, 0, row0 + j * (TILES_PER_CTA * 128), bar);
      tma_load_2d(dst + HALF_BYTES / 2, tmq0, 64, row0 + j * (TILES_PER_CTA * 128), bar);
    };
    if (tid == 0) { load_q(0); load_q(1); }
    const uint32_t part = stage + cw * PART_WG + tid * 16;
    float S[64], O[64];
    uint32_t Q[32], P[32];
    auto fetch_q = [&](int j) {
      mbar_wait(fullQ + 8 * (cw * 2 + (j & 1)), (j >> 1) & 1);
#pragma unroll
      for (int k = 0; k < 8; k++) ldsm_x4(Q[4 * k], Q[4 * k + 1], Q[4 * k + 2], Q[4 * k + 3], (qaddr ^ ((k & 3) << 5)) + (k >> 2) * (HALF_BYTES / 2) + (j & 1) * HALF_BYTES);
    };
    auto refill_q = [&](int j) {
      fence_regs(Q);
      bar_sync(1 + cw, 128);
      if (tid == 0 && j + 2 < SLICES) load_q(j + 2);
    };
#pragma unroll
    for (int i = 0; i < 64; i++) { S[i] = 0.f; O[i] = 0.f; }
    fetch_q(0);
    refill_q(0);
    mbar_wait(fullKV, 0);
    if (cw) bar_arrive(3, 256);
    fence_regs(Q); fence_regs(S);
    wg_fence();
    issue_qk(S, Q, sK);
    wg_commit();
    wg_wait<0>();
    fence_regs(S); fence_regs(Q);
#pragma unroll 1
    for (int j = 0; j < SLICES; j++) {
      if (j + 1 < SLICES) fetch_q(j + 1);
      float s0 = 0.f, s1 = 0.f;
#pragma unroll
      for (int i = 0; i < 16; i++) {
        S[4 * i] = ex2(S[4 * i]); S[4 * i + 1] = ex2(S[4 * i + 1]); S[4 * i + 2] = ex2(S[4 * i + 2]); S[4 * i + 3] = ex2(S[4 * i + 3]);
        s0 += S[4 * i] + S[4 * i + 1]; s1 += S[4 * i + 2] + S[4 * i + 3];
      }
#pragma unroll
      for (int i = 0; i < 32; i++) P[i] = pack_bf16(S[2 * i], S[2 * i + 1]);
      s0 += __shfl_xor_sync(0xffffffffu, s0, 1); s1 += __shfl_xor_sync(0xffffffffu, s1, 1);
      s0 += __shfl_xor_sync(0xffffffffu, s0, 2); s1 += __shfl_xor_sync(0xffffffffu, s1, 2);
      fence_regs(P);
      asm volatile("" : "+f"(s0), "+f"(s1) :: "memory");
      if (j + 1 < SLICES) refill_q(j + 1);
      bar_sync(3 + cw, 256);
      fence_regs(P); fence_regs(O); fence_regs(Q); fence_regs(S);
      wg_fence();
      {
        const uint64_t dv = make_desc(sV, HALF_BYTES, 1024), dk = make_desc(sK, 16, 1024);
#pragma unroll
        for (int k = 0; k < 8; k++) {
          wgmma_rs_nmaj(O, P[4 * k], P[4 * k + 1], P[4 * k + 2], P[4 * k + 3], dv + (uint64_t)((k * 2048) >> 4), k != 0);
          wgmma_rs_kmaj(S, Q[4 * k], Q[4 * k + 1], Q[4 * k + 2], Q[4 * k + 3], dk + (uint64_t)(((k & 3) * 32 + (k >> 2) * HALF_BYTES) >> 4), k != 0);
        }
      }
      wg_commit();
      if (!cw || j + 1 < SLICES) bar_arrive(3 + (cw ^ 1), 256);
      wg_wait<0>();
      fence_regs(O); fence_regs(P); fence_regs(S); fence_regs(Q);
      if (j > 0) mbar_wait(freeb + 8 * cw, (j - 1) & 1);
#pragma unroll
      for (int k = 0; k < 16; k++)
        asm volatile("st.shared.v4.f32 [%0], {%1, %2, %3, %4};\n" ::"r"(part + k * 2048), "f"(O[4 * k]), "f"(O[4 * k + 1]), "f"(O[4 * k + 2]), "f"(O[4 * k + 3]) : "memory");
      if ((lane & 3) == 0) asm volatile("st.shared.v2.f32 [%0], {%1, %2};\n" ::"r"(part + 32768 - tid * 14), "f"(s0), "f"(s1) : "memory");
      asm volatile("fence.proxy.async.shared::cta;\n" ::: "memory");
      __syncwarp();
      if (lane == 0) mbar_arrive_local(done + 8 * (cw * SLICES + j));
    }
  }
}
template <bool HELP>
__global__ void __cluster_dims__(CL, 1, 1) __launch_bounds__(384, 1)
attn_kernel(const DqCtx dq, const __nv_bfloat16* __restrict__ q, __nv_bfloat16* __restrict__ out, const uint32_t zero, const int fused,
            const __grid_constant__ CUtensorMap tmq, const __grid_constant__ CUtensorMap tmq0) {
  extern __shared__ uint8_t smem_raw[];
  const uint32_t sbase = (smem_u32(smem_raw) + 1023u) & ~1023u;
  const uint32_t sK = sbase, sV = sbase + NK * TILE_BYTES, sQ = sbase + (NK + NV) * TILE_BYTES;
  const uint32_t bars = sbase + (NK + NV + 1) * TILE_BYTES;
  const uint32_t fullK = bars, fullV = bars + 8 * NK, emptyK = bars + 8 * (NK + NV), emptyV = emptyK + 8 * NK;
  const uint32_t fullQ = emptyV + 8 * NV, emptyQ = fullQ + 8, fullR = emptyQ + 8, sflag = fullR + 16, full0 = fullR + 24, rawB = fullR + 32, fullQ0 = rawB + 16, fullP = fullQ0 + 16;
  const uint32_t sRaw = sV + TILE_BYTES;

  const int cta = blockIdx.x;
  if (HELP && __builtin_expect(cta >= NCTAS, 0)) { helper(dq, &tmq0, sbase, cta - NCTAS); return; }
  const int warp = __shfl_sync(0xffffffffu, (int)(threadIdx.x >> 5), 0);
  const int lane = threadIdx.x & 31;
  const int wg = warp >> 2;
  const uint32_t rank = cta & (CL - 1);
  const int h = cta >> 5;
  const int row0 = cta * (TILES_PER_CTA * 128);
  constexpr int TOTAL = TILES_PER_CTA * NBLK - HELP;

  const uint32_t t_start = clock();
  const DqLane L(cta, lane);
  DqTask task;
  uint32_t epoch = 0;
  const unsigned* epoch_p = cnt_line(region(dq.scr, h, 0), warp == 3 ? 3 : DqTask::tile_of(warp)) + 2;
  if (__builtin_expect(wg == 0, 1)) {
    if (warp == 3) {
      if (fused) epoch = *reinterpret_cast<const volatile unsigned*>(epoch_p);
      if (lane == 0) {
        mbar_init(rawB, 1); mbar_init(rawB + 8, 1); mbar_init(fullQ0, 1); mbar_init(fullQ0 + 8, 1);
        asm volatile("fence.proxy.async.shared::cta;\n" ::: "memory");
        if (fused) {
          const uint8_t* gc = reinterpret_cast<const uint8_t*>(dq.qk) + (size_t)h * SKV * DH * 4;
          mbar_expect_tx(rawB, TILE_BYTES + 512);
          bulk_load(sRaw, gc, TILE_BYTES, rawB);
          bulk_load(bars + ZS_OFF, dq.kz + h * NBLK * DH, 256, rawB);
          bulk_load(bars + ZS_OFF + 256, dq.ks + h * NBLK * DH, 256, rawB);
          mbar_expect_tx(rawB + 8, TILE_BYTES);
          bulk_load(sRaw + TILE_BYTES, gc + TILE_BYTES, TILE_BYTES, rawB + 8);
        }
        LS(15);
        while ((uint32_t)clock() - t_start < Q_DELAY) { }
        mbar_expect_tx(fullQ0, TILE_BYTES / 2);
        tma_load_2d(sQ, &tmq0, 0, row0, fullQ0);
        tma_load_2d(sQ + HALF_BYTES, &tmq0, 64, row0, fullQ0);
        LS(14);
      }
      __syncwarp();
      if (lane == 0) {
        for (int s = 0; s < NK; s++) { mbar_init(fullK + 8 * s, 1); mbar_init(emptyK + 8 * s, 8 * CL); }
        for (int s = 0; s < NV; s++) { mbar_init(fullV + 8 * s, 1); mbar_init(emptyV + 8 * s, 8 * CL); }
        mbar_init(fullQ, 1); mbar_init(emptyQ, 8); mbar_init(fullR, 1); mbar_init(fullR + 8, 1); mbar_init(full0, 8);
        if (HELP) mbar_init(fullP, 1);
        if (fused) mbar_arrive_local(fullK);
        asm volatile("fence.mbarrier_init.release.cluster;\n" ::: "memory");
        asm volatile("fence.proxy.async.shared::cta;\n" ::: "memory");
      }
      __syncwarp();
      asm volatile("barrier.cluster.arrive.relaxed.aligned;\n" ::: "memory");
      ST2(1);
    } else {
      asm volatile("barrier.cluster.arrive.relaxed.aligned;\n" ::: "memory");
      if (fused) {
        const int t = DqTask::tile_of(warp);
        task.load_tile(dq, L, h, t, lane);
        epoch = *reinterpret_cast<const volatile unsigned*>(epoch_p);
        if (warp) LS(warp * 4);
      }
    }
  } else {
    asm volatile("barrier.cluster.arrive.relaxed.aligned;\n" ::: "memory");
  }
  uint32_t wg2 = wg;
  asm volatile("" : "+r"(wg2));
  if (wg2 == 0) {
    const uint32_t todo_a = bars + 224 + 4 * warp;
    auto defer = [&](int t) { if (lane == 0) asm volatile("red.shared.or.b32 [%0], %1;\n" ::"r"(todo_a), "r"(1u << t) : "memory"); };
    if (lane == 0) asm volatile("st.shared.u32 [%0], %1;\n" ::"r"(todo_a), "r"(0u) : "memory");
    if (warp != 3 && fused) {
      const int t = DqTask::tile_of(warp);
      if (task.store_tile(L, region(dq.scr, h, epoch & 1), t, lane)) defer(t);
      LS(warp * 4 + 2);
    }
    asm volatile("setmaxnreg.dec.sync.aligned.u32 40;\n");
    asm volatile("barrier.cluster.wait.aligned;\n" ::: "memory");
    if (warp == 3) {
      ST2(2);
    }
    uint8_t* const reg = region(dq.scr, h, epoch & 1);
    if (__builtin_expect(warp == 3, 1)) {
      ST2(3);
      const uint8_t* img = reg + rank * SLICE;
      const unsigned* cnt = cnt_line(reg, lane);
      uint32_t ready = fused ? 0u : ~0u;
      auto poll = [&](int t) {
        unsigned v = 0;
        if ((unsigned)(lane - (t - 1)) < POLLW) asm volatile("ld.relaxed.gpu.global.u32 %0, [%1];\n" : "=r"(v) : "l"(cnt) : "memory");
        return v;
      };
      unsigned pa = 0, pb = 0, pc = 0;
      auto need = [&](int t) {
        if ((ready >> t) & 1) return;
        unsigned n = 0;
        do {
          ready |= __ballot_sync(0xffffffffu, poll(t) >= LL_HINT);
          if (++n > (1u << 24)) __trap();
        } while (!((ready >> t) & 1));
      };
      if (lane == 0) asm volatile("st.shared.u32 [%0], %1;\n" ::"r"(sflag), "r"(epoch) : "memory");
      if (fused) {
        if (lane == 0) asm volatile("red.relaxed.gpu.global.add.u32 [%0], 1;\n" ::"l"(cnt_line(reg, LINE_FINAL)) : "memory");
        if (__builtin_expect(epoch == 0, 0)) {
          wait_final(reg);
          ready = ~0u;
        }
      }
      int ks = 0, kph = 1, vs = 0, vph = 1, i0 = 0;
      while ((uint32_t)clock() - t_start < Q_DELAY1) { }
      if (lane == 0) {
        mbar_expect_tx(fullQ0 + 8, TILE_BYTES / 2);
        tma_load_2d(sQ + 64 * 128, &tmq0, 0, row0 + 64, fullQ0 + 8);
        tma_load_2d(sQ + HALF_BYTES + 64 * 128, &tmq0, 64, row0 + 64, fullQ0 + 8);
      }
      __syncwarp();
      if (fused) {
        if (ready != ~0u) {
          while ((uint32_t)clock() - t_start < POLL0) { }
          LS(0);
          unsigned n = 0;
          do {
            ready |= __ballot_sync(0xffffffffu, poll(2) >= LL_HINT);
            if (++n > (1u << 24)) __trap();
          } while ((ready & 6u) != 6u);
        }
        if (lane == 0) {
          mbar_expect_tx(fullK + 8, TILE_BYTES);
          bulk_load_mc(sK + TILE_BYTES + rank * SLICE, img + 2 * TILE_BYTES, SLICE, fullK + 8, (uint16_t)((1 << CL) - 1));
          mbar_expect_tx(fullV, TILE_BYTES);
          bulk_load_mc(sV + rank * SLICE, img + TILE_BYTES, SLICE, fullV, (uint16_t)((1 << CL) - 1));
        }
        ST2(6); ST2(7);
        i0 = 2; ks = 2; vs = 1;
      }
      for (int i = i0; i <= TOTAL; i++) {
        PR(0);
        const unsigned early = (i >= EARLY_FROM && i <= NBLK && ready != ~0u) ? poll(2 * (i & (NBLK - 1))) : 0u;
        PR(1);
        if (i < TOTAL) {
          if (i >= NK) mbar_wait(emptyK + 8 * ks, kph);
          PR(2);
          if (i <= NBLK) { ready |= __ballot_sync(0xffffffffu, early >= LL_HINT); if (i > 0 || !fused) need(2 * (i & (NBLK - 1))); }
          if (lane == 0 && (i > 0 || !fused)) {
            mbar_expect_tx(fullK + 8 * ks, TILE_BYTES);
            bulk_load_mc(sK + ks * TILE_BYTES + rank * SLICE, img + (size_t)((i & (NBLK - 1)) + (HELP && i >= TOTAL - NBLK + 1 + HBLK)) * (2 * TILE_BYTES), SLICE, fullK + 8 * ks, (uint16_t)((1 << CL) - 1));
          }
          PR(3);
          if (i == 0) ST2(0);
          if (i == 1) ST2(6);
          if (i == 2) ST2(4);
          if (++ks == NK) { ks = 0; kph ^= 1; }
        }
        if (i > 0) {
          mbar_wait(emptyV + 8 * vs, vph ^ (uint32_t)(vs != 0 && fused));
          PR(4);
          if (i <= NBLK) need(2 * i - 1);
          if (i == 1) ST2(7);
          if (lane == 0) {
            mbar_expect_tx(fullV + 8 * vs, TILE_BYTES);
            bulk_load_mc(sV + vs * TILE_BYTES + rank * SLICE, img + (size_t)(((i - 1) & (NBLK - 1)) + (HELP && i - 1 >= TOTAL - NBLK + 1 + HBLK)) * (2 * TILE_BYTES) + TILE_BYTES, SLICE, fullV + 8 * vs, (uint16_t)((1 << CL) - 1));
          }
          PR(5);
          if (i == 2) ST2(8);
          if (++vs == NV) { vs = 0; vph ^= 1; }
        }
        const int p = (i & (NBLK - 1)) - QFIRST;
        if (p >= 0 && p < QP && i < (TILES_PER_CTA - 1) * NBLK) {
          if (p == 0) {
            mbar_wait(emptyQ, ((i >> 4) & 1));
            if (lane == 0) mbar_expect_tx(fullQ, TILE_BYTES);
          }
          if (lane == 0) tma_load_2d(sQ + (p & 1) * HALF_BYTES + (p >> 1) * (QROWS * 128), &tmq, (p & 1) * 64, row0 + ((i >> 4) + 1) * 128 + (p >> 1) * QROWS, fullQ);
        }
      }
      if (HELP) {
        unsigned v, n = 0;
        do {
          asm volatile("ld.acquire.gpu.global.u32 %0, [%1];\n" : "=r"(v) : "l"(cnt_line(region(dq.scr, h, 0), LINE_PART + (cta & (SLICES - 1))) + (lane & 1)) : "memory");
          if (++n > (1u << 24)) __trap();
        } while (!__all_sync(0xffffffffu, v == epoch + 1));
        asm volatile("fence.proxy.async.global;\n" ::: "memory");
        mbar_wait(emptyK + 8 * ks, kph);
        if (lane == 0) {
          const uint8_t* part = g_part + (size_t)cta * PART_BYTES;
          mbar_expect_tx(fullP, 2 * TILE_BYTES + 512);
          bulk_load(sK + ks * TILE_BYTES, part, TILE_BYTES, fullP);
          bulk_load(bars + ZS_OFF, part + TILE_BYTES, 256, fullP);
          bulk_load(sQ, part + PART_WG, TILE_BYTES, fullP);
          bulk_load(bars + ZS_OFF + 256, part + PART_WG + TILE_BYTES, 256, fullP);
        }
      }
      if (fused && (cta & (SLICES - 1)) == 0) {
        wait_final(reg);
        if (lane >= 1 && lane <= 4) cnt_line(region(dq.scr, h, 0), lane)[2] = epoch + 1;
      }
    } else if (fused) {
      while ((uint32_t)clock() - t_start < B_DELAY) { }
      task.load_tile(dq, L, h, DqTask::tile_of(3 + warp), lane);
#pragma unroll 1
      for (int u = 3 + warp; u < 2 * NBLK; u += 3) {
        const int t = DqTask::tile_of(u);
        if (task.store_tile(L, reg, t, lane)) defer(t);
        if (u + 3 < 2 * NBLK) task.load_tile(dq, L, h, DqTask::tile_of(u + 3), lane);
      }
      __syncwarp();
      uint32_t todo;
      asm volatile("ld.shared.u32 %0, [%1];\n" : "=r"(todo) : "r"(todo_a) : "memory");
#pragma unroll 1
      while (__builtin_expect(todo != 0, 0)) {
        const int t = __ffs(todo) - 1;
        todo &= todo - 1;
        dq_rows_any(dq, L, reg, h, t, lane);
        __syncwarp();
        if (lane == 0) asm volatile("red.relaxed.gpu.global.add.u32 [%0], 1;\n" ::"l"(cnt_line(reg, t)) : "memory");
      }
      asm volatile("fence.proxy.async.global;\n" ::: "memory");
      __syncwarp();
      if (lane == 0) asm volatile("red.release.gpu.global.add.u32 [%0], 1;\n" ::"l"(cnt_line(reg, LINE_FINAL)) : "memory");
      uint8_t* other = region(dq.scr, h, (epoch & 1) ^ 1);
      uint8_t* e = other + (lane >> 4) * HALF_BYTES + (L.rr0 + ((lane >> 3) & 1)) * 128 + (lane & 7) * 16;
#pragma unroll 1
      for (int t = warp; t < 2 * NBLK; t += 3) {
        *reinterpret_cast<uint4*>(e + t * TILE_BYTES) = make_uint4(~0u, ~0u, ~0u, ~0u);
        *reinterpret_cast<uint4*>(e + t * TILE_BYTES + 1024) = make_uint4(~0u, ~0u, ~0u, ~0u);
      }
      if ((cta & (SLICES - 1)) == 1 && warp == 0) { *cnt_line(other, lane) = 0; if (lane == 0) *cnt_line(other, LINE_FINAL) = 0; }
    }
    __syncwarp();
    asm volatile("barrier.cluster.arrive.relaxed.aligned;\n" ::: "memory");
  } else {
    asm volatile("barrier.cluster.wait.aligned;\n" ::: "memory");
    if (fused) {
      mbar_wait(rawB, 0);
      if (warp == 4) LS(21);
      uint2 z0, sc0;
      asm volatile("ld.shared.v2.u32 {%0, %1}, [%2];\n" : "=r"(z0.x), "=r"(z0.y) : "r"(bars + ZS_OFF + lane * 8));
      asm volatile("ld.shared.v2.u32 {%0, %1}, [%2];\n" : "=r"(sc0.x), "=r"(sc0.y) : "r"(bars + ZS_OFF + 256 + lane * 8));
      mbar_wait(rawB + 8 * (((warp - 4) * RAWN) >> 3), 0);
      if (warp == 4) LS(3);
      if (warp == 8) LS(7);
      const uint32_t src = sRaw + (warp - 4) * 8192 + lane * 16;
      const uint32_t dst = sK + (lane >> 4) * HALF_BYTES + (warp - 4) * 2048 + (((lane >> 1) & 7) << 4) + (lane & 1) * 8;
      const uint32_t ns0 = sc0.x, ns1 = sc0.y;
      uint32_t any = 0;
      auto ld4 = [&](uint4 (&x)[4], int g) {
#pragma unroll
        for (int i = 0; i < 4; i++)
          asm volatile("ld.shared.v4.u32 {%0, %1, %2, %3}, [%4];\n" : "=r"(x[i].x), "=r"(x[i].y), "=r"(x[i].z), "=r"(x[i].w) : "r"(src + (g + i) * 512));
      };
      auto cv4 = [&](const uint4 (&x)[4], int g, auto k0_c) {
        constexpr int K0 = decltype(k0_c)::value;
#pragma unroll
        for (int i = 0; i < 4; i++) {
          any |= x[i].x | x[i].y | x[i].z | x[i].w;
          asm volatile("st.shared.v2.b32 [%0], {%1, %2};\n" ::"r"(((dst + g * 128) ^ ((K0 + i) << 4)) + (K0 + i) * 128), "r"(scale_key<true>(dq_pair_small(x[i].x, x[i].y, z0.x, ns0))),
                       "r"(scale_key<true>(dq_pair_small(x[i].z, x[i].w, z0.y, ns1))) : "memory");
        }
      };
      uint4 xa[4], xb[4];
      ld4(xa, 0);
#pragma unroll
      for (int g = 0; g < 16; g += 8) {
        ld4(xb, g + 4);
        cv4(xa, g, IntC<0>());
        if (g == 0) ld4(xa, 8);
        cv4(xb, g, IntC<4>());
      }
      if (__builtin_expect(__any_sync(0xffffffffu, any >= 256u), 0)) {
#pragma unroll 1
        for (int i = 0; i < 16; i++) {
          int4 a;
          asm volatile("ld.shared.v4.u32 {%0, %1, %2, %3}, [%4];\n" : "=r"(a.x), "=r"(a.y), "=r"(a.z), "=r"(a.w) : "r"(src + i * 512));
          asm volatile("st.shared.v2.b32 [%0], {%1, %2};\n" ::"r"((dst ^ ((i & 7) << 4)) + i * 128), "r"(scale_key(dq_pair_any(a.x, a.y, z0.x, sc0.x))),
                       "r"(scale_key(dq_pair_any(a.z, a.w, z0.y, sc0.y))) : "memory");
        }
      }
      asm volatile("fence.proxy.async.shared::cta;\n" ::: "memory");
      __syncwarp();
      if (lane == 0) mbar_arrive_local(full0);
      if (lane < CL) { mbar_arrive_cluster(emptyV + 8, lane); mbar_arrive_cluster(emptyV + 16, lane); }
      if (warp == 4) LS(11);
      if (warp == 11) LS(9);
    }
    mbar_wait(fullQ0 + (warp & 8), 0);
    if (warp == 4) LS(12);
    if (warp == 8) LS(13);
    asm volatile("setmaxnreg.inc.sync.aligned.u32 232;\n");
    uint32_t tid;
    asm volatile("mov.u32 %0, %%tid.x;\n" : "=r"(tid));
    const int my_bar = tid >> 7, other_bar = 3 - my_bar;
    const int cw = my_bar - 1;
    const int wq = (tid >> 5) & 3;
    const int c = lane & 3;
    const int myrow = row0 + cw * 64 + wq * 16 + (lane >> 2);
    __nv_bfloat16* optr = out + (size_t)myrow * DH + 8 * c;
    const uint32_t qaddr = sQ + (cw * 64 + wq * 16 + (lane & 15)) * 128 + ((((lane >> 4) ^ lane) & 7) << 4);

    float S[64], O[64];
    uint32_t P[32], Q[32];
    float l0 = 0.f, l1 = 0.f;
    float s0, s1;
    uint32_t bad = 0;
#pragma unroll
    for (int i = 0; i < 64; i++) { S[i] = 0.f; O[i] = 0.f; }

    auto ldsm_q = [&]() {
#pragma unroll
      for (int k = 0; k < 8; k++) ldsm_x4(Q[4 * k], Q[4 * k + 1], Q[4 * k + 2], Q[4 * k + 3], (qaddr ^ ((k & 3) << 5)) + (k >> 2) * HALF_BYTES);
    };
    auto release = [&](uint32_t bar) {
      if (lane < CL) mbar_arrive_cluster(bar, lane);
    };
    auto exps = [&](float (&hist)[8][2]) {
#pragma unroll
      for (int k = 0; k < 8; k++) {
        float a0 = k ? hist[k - 1][0] : 0.f, a1 = k ? hist[k - 1][1] : 0.f;
#pragma unroll
        for (int j = 2 * k; j < 2 * k + 2; j++) {
          S[4 * j + 0] = ex2(S[4 * j + 0]); S[4 * j + 1] = ex2(S[4 * j + 1]); S[4 * j + 2] = ex2(S[4 * j + 2]); S[4 * j + 3] = ex2(S[4 * j + 3]);
          if (j == 0) { a0 = S[0] + S[1]; a1 = S[2] + S[3]; }
          else { a0 += S[4 * j + 0]; a0 += S[4 * j + 1]; a1 += S[4 * j + 2]; a1 += S[4 * j + 3]; }
        }
        hist[k][0] = a0; hist[k][1] = a1;
      }
    };
    auto convert_p = [&]() {
#pragma unroll
      for (int i = 0; i < 32; i++) P[i] = pack_bf16(S[2 * i], S[2 * i + 1]);
    };
    auto pack_o = [&](float r0, float r1) {
      uint32_t nf = 0;
#pragma unroll
      for (int J = 0; J < 4; J++) {
        float* o = &O[16 * J];
        asm volatile("{\n.reg .f32 t<16>;\n.reg .b32 u<8>, z, a, b;\n"
            "mul.f32 t0, %0, %17;\nmul.f32 t1, %1, %17;\nmul.f32 t2, %2, %18;\nmul.f32 t3, %3, %18;\n"
            "mul.f32 t4, %4, %17;\nmul.f32 t5, %5, %17;\nmul.f32 t6, %6, %18;\nmul.f32 t7, %7, %18;\n"
            "mul.f32 t8, %8, %17;\nmul.f32 t9, %9, %17;\nmul.f32 t10, %10, %18;\nmul.f32 t11, %11, %18;\n"
            "mul.f32 t12, %12, %17;\nmul.f32 t13, %13, %17;\nmul.f32 t14, %14, %18;\nmul.f32 t15, %15, %18;\n"
            "cvt.rn.bf16x2.f32 u0, t1, t0;\ncvt.rn.bf16x2.f32 u1, t5, t4;\ncvt.rn.bf16x2.f32 u2, t9, t8;\ncvt.rn.bf16x2.f32 u3, t13, t12;\n"
            "cvt.rn.bf16x2.f32 u4, t3, t2;\ncvt.rn.bf16x2.f32 u5, t7, t6;\ncvt.rn.bf16x2.f32 u6, t11, t10;\ncvt.rn.bf16x2.f32 u7, t15, t14;\n"
            "mov.b32 z, 0;\n"
            "fma.rn.bf16x2 a, u0, z, z;\nfma.rn.bf16x2 b, u4, z, %16;\nfma.rn.bf16x2 a, u1, z, a;\nfma.rn.bf16x2 b, u5, z, b;\n"
            "fma.rn.bf16x2 a, u2, z, a;\nfma.rn.bf16x2 b, u6, z, b;\nfma.rn.bf16x2 a, u3, z, a;\nfma.rn.bf16x2 b, u7, z, b;\n"
            "or.b32 %16, a, b;\n"
            "mov.b32 %0, u0;\nmov.b32 %1, u1;\nmov.b32 %2, u2;\nmov.b32 %3, u3;\n"
            "mov.b32 %4, u4;\nmov.b32 %5, u5;\nmov.b32 %6, u6;\nmov.b32 %7, u7;\n}\n"
            : "+f"(o[0]), "+f"(o[1]), "+f"(o[2]), "+f"(o[3]), "+f"(o[4]), "+f"(o[5]), "+f"(o[6]), "+f"(o[7]),
              "+f"(o[8]), "+f"(o[9]), "+f"(o[10]), "+f"(o[11]), "+f"(o[12]), "+f"(o[13]), "+f"(o[14]), "+f"(o[15]), "+r"(nf)
            : "f"(r0), "f"(r1));
      }
      return (nf & 0x7fff7fffu) != 0;
    };
    auto store_o = [&](int tile) {
      __nv_bfloat16* o = optr + (size_t)tile * 128 * DH;
#pragma unroll
      for (int J = 0; J < 4; J++) {
        asm volatile("st.global.v4.b32 [%0], {%1, %2, %3, %4};\n" :: "l"(o + 32 * J), "f"(O[16 * J]), "f"(O[16 * J + 1]), "f"(O[16 * J + 2]), "f"(O[16 * J + 3]) : "memory");
        asm volatile("st.global.v4.b32 [%0], {%1, %2, %3, %4};\n" :: "l"(o + 8 * DH + 32 * J), "f"(O[16 * J + 4]), "f"(O[16 * J + 5]), "f"(O[16 * J + 6]), "f"(O[16 * J + 7]) : "memory");
      }
    };
#define EPI_MODE 0
#define STORE_AT_SETTLE { if (pack_o(l0, l1)) bad |= 1u << ((i >> 4) - 1); store_o((i >> 4) - 1); }
    auto finish_sums = [&]() {
      l0 += __shfl_xor_sync(0xffffffffu, l0, 1); l1 += __shfl_xor_sync(0xffffffffu, l1, 1);
      l0 += __shfl_xor_sync(0xffffffffu, l0, 2); l1 += __shfl_xor_sync(0xffffffffu, l1, 2);
      const bool ok = l0 >= SUM_LO && l0 <= SUM_HI && l1 >= SUM_LO && l1 <= SUM_HI;
      l0 = -rcp_fast(l0); l1 = -rcp_fast(l1);
      return ok;
    };
    auto settle = [&](int i) {
      const int blk = i & (NBLK - 1);
      if (blk == 0) {
        if (i > 0) STORE_AT_SETTLE;
        l0 = 0.f; l1 = 0.f;
      }
      l0 += s0; l1 += s1;
      if (blk == NBLK - 1) { if (!finish_sums()) bad |= 1u << (i >> 4); }
    };

    int ks = 0, kph = 0, vs = 0, vph = 0;
    if (cw == 1) bar_arrive(1, 256);
    __syncwarp();
    ldsm_q();

    {
      if (warp == 4) ST2(9);
      if (fused) mbar_wait(full0, 0); else mbar_wait(fullK, 0);
      if (warp == 4) ST2(10);
      fence_regs(Q); fence_regs(S);
      wg_fence();
      issue_qk(S, Q, sK);
      wg_commit();
      if (lane == 0) mbar_arrive_local(emptyQ);
      ks = 1;
      if (warp == 4) ST2(11);
      wg_wait<0>();
      fence_regs(S);
      if (warp == 4) ST2(12);
      release(emptyK);
      float hist[8][2];
      exps(hist);
      convert_p();
      s0 = hist[7][0]; s1 = hist[7][1];
      if (warp == 4) ST2(13);
      mbar_wait(fullK + 8 * ks, kph);
      if (warp == 4) ST2(14);
      mbar_wait(fullV + 8 * vs, vph);
      if (warp == 4) ST2(15);
    }
    auto iteration = [&](auto pre_c, int i) {
      constexpr bool PRE = decltype(pre_c)::value;
      const int blk = PRE ? NBLK - 2 : (i & (NBLK - 1));
      const uint32_t kaddr = sK + ks * TILE_BYTES, vaddr = sV + vs * TILE_BYTES;
      const uint32_t relK = emptyK + 8 * ks, relV = emptyV + 8 * vs;
      if (++ks == NK) { ks = 0; kph ^= 1; }
      if (++vs == NV) { vs = 0; vph ^= 1; }
      const uint32_t nextK = fullK + 8 * ks, nextV = fullV + 8 * vs;
      BAR_SYNC_MINE;
      fence_regs(Q); fence_regs(S);
      wg_fence();
      issue_qk(S, Q, kaddr);
      wg_commit();
      settle(i);
      fence_regs(P); fence_regs(O);
      wg_fence();
      issue_pv(O, P, vaddr, blk != 0);
      wg_commit();
      BAR_ARRIVE_OTHER;
      if (PRE) mbar_wait(fullQ, (((i + 2) >> 4) & 1) ^ 1);
      else if (blk == NBLK - 1 && lane == 0) mbar_arrive_local(emptyQ);
      wg_wait<1>();
      fence_regs(S); fence_regs(Q);
      release(relK);
      if (PRE) { if (LDSM_POS == 0) ldsm_q(); }
      float hist[8][2];
      exps(hist);
      const uint32_t tK = mbar_test(nextK, tieu(kph, hist[SPLIT - 1][0], zero));
      const uint32_t tV = mbar_test(nextV, tieu(vph, hist[SPLIT - 1][1], zero));
      wg_wait<0>();
      const bool okK = __all_sync(0xffffffffu, tK) || (i + 2 >= TOTAL);
      const bool okV = __all_sync(0xffffffffu, tV);
      fence_regs(O); fence_regs(P);
      release(relV);
      convert_p();
      s0 = hist[7][0]; s1 = hist[7][1];
      if (PRE && LDSM_POS == 1) ldsm_q();
      if (!PRE && blk == NBLK - 1) {
      }
      if (!okK) mbar_wait(nextK, kph);
      if (!okV) mbar_wait(nextV, vph);
    };
#pragma unroll 1
    for (int i = 0; i < TOTAL - 1; i++) {
      if ((i & (NBLK - 1)) == NBLK - 2 && i + 2 < TOTAL) iteration(BoolC<true>(), i);
      else iteration(BoolC<false>(), i);
    }
    asm volatile("barrier.cluster.arrive.relaxed.aligned;\n" ::: "memory");
    {
      settle(TOTAL - 1);
      auto fetch_share = [&]() {
        static_assert(!HELP || TOTAL % NK == 0, "the share of the first warpgroup lands in stage 0");
        const uint32_t part = (cw ? sQ : sK) + (tid & 127) * 16;
        mbar_wait(fullP, 0);
        float pl0, pl1;
        asm volatile("ld.shared.v2.f32 {%0, %1}, [%2];\n" : "=f"(pl0), "=f"(pl1) : "r"(bars + ZS_OFF + cw * 256 + ((tid & 127) >> 2) * 8) : "memory");
#pragma unroll
        for (int k = 0; k < 16; k++)
          asm volatile("ld.shared.v4.f32 {%0, %1, %2, %3}, [%4];\n" : "=f"(S[4 * k]), "=f"(S[4 * k + 1]), "=f"(S[4 * k + 2]), "=f"(S[4 * k + 3]) : "r"(part + k * 2048) : "memory");
        if ((lane & 3) == 0) { l0 += pl0; l1 += pl1; }
      };
      auto add_share = [&]() {
#pragma unroll
        for (int k = 0; k < 64; k++) O[k] += S[k];
      };
      if (HELP && H_EARLY(cw)) { fetch_share(); add_share(); }
      BAR_SYNC_MINE;
      fence_regs(P); fence_regs(O);
      wg_fence();
      issue_pv(O, P, sV + vs * TILE_BYTES, 1);
      wg_commit();
      BAR_ARRIVE_OTHER;
      if (HELP) {
        if (!H_EARLY(cw)) fetch_share();
        if (!finish_sums()) bad |= 1u << (TILES_PER_CTA - 1);
      }
      wg_wait<0>();
      fence_regs(O);
      if (HELP && !H_EARLY(cw)) add_share();
      if (pack_o(l0, l1)) bad |= 1u << (TILES_PER_CTA - 1);
      store_o(TILES_PER_CTA - 1);
      const bool redo = wg_any(bad != 0, 5 + cw);
      if (cw == 0) bar_sync(1, 256);
      if (__builtin_expect(redo, 0)) {
        static_assert(NK == 3 && NV == 3, "the last block uses stage (TOTAL - 1) % 3");
        const int st = (TOTAL + cw) % 3;
        const uint32_t kaddr = sK + st * TILE_BYTES, vaddr = sV + st * TILE_BYTES, bar = fullR + 8 * cw;
        uint32_t par;
        asm volatile("ld.shared.u32 %0, [%1];\n" : "=r"(par) : "r"(sflag) : "memory");
        uint8_t* img = region(dq.scr, h, par & 1);
        if (fused) wait_final(img);
        uint32_t ph = 0;
#pragma unroll 1
        for (int tile = 0; tile < TILES_PER_CTA; tile++) {
          if (!wg_any((bad >> tile) & 1, 5 + cw)) continue;
          const uint32_t* qp = reinterpret_cast<const uint32_t*>(q + ((size_t)myrow + tile * 128) * DH) + c;
          float m0 = 0.f, m1 = 0.f;
#pragma unroll 1
          for (int blk = 0; blk < NBLK; blk++) {
#pragma unroll
            for (int k = 0; k < 8; k++) {
              Q[4 * k] = __ldg(qp + 8 * k); Q[4 * k + 1] = __ldg(qp + 8 * k + 4 * DH); Q[4 * k + 2] = __ldg(qp + 8 * k + 4); Q[4 * k + 3] = __ldg(qp + 8 * k + 4 + 4 * DH);
            }
            if ((tid & 127) == 0) {
              asm volatile("fence.proxy.async.global;\n" ::: "memory");
              mbar_expect_tx(bar, 2 * TILE_BYTES);
              bulk_load(kaddr, img + (size_t)blk * (2 * TILE_BYTES), TILE_BYTES, bar);
              bulk_load(vaddr, img + (size_t)blk * (2 * TILE_BYTES) + TILE_BYTES, TILE_BYTES, bar);
            }
            mbar_wait(bar, ph);
            ph ^= 1;
            fence_regs(Q); fence_regs(S);
            wg_fence();
            issue_qk(S, Q, kaddr);
            wg_commit();
            wg_wait<0>();
            fence_regs(S); fence_regs(Q);
            float x0 = fmaxf(S[0], S[1]), x1 = fmaxf(S[2], S[3]);
#pragma unroll
            for (int j = 1; j < 16; j++) { x0 = fmaxf(x0, fmaxf(S[4 * j], S[4 * j + 1])); x1 = fmaxf(x1, fmaxf(S[4 * j + 2], S[4 * j + 3])); }
            x0 = fmaxf(x0, __shfl_xor_sync(0xffffffffu, x0, 1)); x1 = fmaxf(x1, __shfl_xor_sync(0xffffffffu, x1, 1));
            x0 = fmaxf(x0, __shfl_xor_sync(0xffffffffu, x0, 2)); x1 = fmaxf(x1, __shfl_xor_sync(0xffffffffu, x1, 2));
            x0 = fmaxf(x0, -3.0e38f); x1 = fmaxf(x1, -3.0e38f);
            if (blk == 0) { l0 = 0.f; l1 = 0.f; }
            else {
              x0 = fmaxf(x0, m0); x1 = fmaxf(x1, m1);
              const float a0 = ex2(m0 - x0), a1 = ex2(m1 - x1);
              l0 *= a0; l1 *= a1;
#pragma unroll
              for (int j = 0; j < 16; j++) { O[4 * j] *= a0; O[4 * j + 1] *= a0; O[4 * j + 2] *= a1; O[4 * j + 3] *= a1; }
            }
            m0 = x0; m1 = x1;
#pragma unroll
            for (int j = 0; j < 16; j++) {
              S[4 * j] = ex2(S[4 * j] - m0); S[4 * j + 1] = ex2(S[4 * j + 1] - m0); S[4 * j + 2] = ex2(S[4 * j + 2] - m1); S[4 * j + 3] = ex2(S[4 * j + 3] - m1);
              l0 += S[4 * j] + S[4 * j + 1]; l1 += S[4 * j + 2] + S[4 * j + 3];
            }
            convert_p();
            fence_regs(P); fence_regs(O);
            wg_fence();
            issue_pv(O, P, vaddr, blk != 0);
            wg_commit();
            wg_wait<0>();
            fence_regs(O); fence_regs(P);
            bar_sync(5 + cw, 128);
          }
          finish_sums();
          pack_o(l0, l1);
          store_o(tile);
        }
      }
    }
  }
  asm volatile("barrier.cluster.wait.aligned;\n" ::: "memory");
}

}

typedef CUresult (*EncodeTiledFn)(CUtensorMap*, CUtensorMapDataType, cuuint32_t, void*, const cuuint64_t*, const cuuint64_t*, const cuuint32_t*,
                                  const cuuint32_t*, CUtensorMapInterleave, CUtensorMapSwizzle, CUtensorMapL2promotion, CUtensorMapFloatOOBfill);

extern "C" void kernel_launch(void* const* d_in, const int* in_sizes, int n_in, void* d_out, int out_size) {
  const int* qk = (const int*)d_in[1];
  const int* qv = (const int*)d_in[2];
  const __nv_bfloat16* ks = (const __nv_bfloat16*)d_in[3];
  const __nv_bfloat16* kz = (const __nv_bfloat16*)d_in[4];
  const __nv_bfloat16* vs = (const __nv_bfloat16*)d_in[5];
  const __nv_bfloat16* vz = (const __nv_bfloat16*)d_in[6];
  __nv_bfloat16* out = (__nv_bfloat16*)d_out;
  static EncodeTiledFn encode = nullptr;
  static int fused = 0, help = 0;
  static uint8_t* scr = nullptr;
  if (!encode) {
    void* sp = nullptr;
    cudaGetSymbolAddress(&sp, g_scratch);
    scr = (uint8_t*)(((uintptr_t)sp + PAGE - 1) & ~(uintptr_t)(PAGE - 1));
    cudaFuncSetAttribute(attn_kernel<false>, cudaFuncAttributeMaxDynamicSharedMemorySize, SMEM_BYTES);
    cudaFuncSetAttribute(attn_kernel<true>, cudaFuncAttributeMaxDynamicSharedMemorySize, SMEM_BYTES);
    {
      cudaLaunchConfig_t cfg = {};
      cfg.gridDim = dim3(NCTAS); cfg.blockDim = dim3(384); cfg.dynamicSmemBytes = SMEM_BYTES;
      cudaLaunchAttribute at[1];
      at[0].id = cudaLaunchAttributeClusterDimension; at[0].val.clusterDim.x = CL; at[0].val.clusterDim.y = 1; at[0].val.clusterDim.z = 1;
      cfg.attrs = at; cfg.numAttrs = 1;
      int nc = 0;
      fused = cudaOccupancyMaxActiveClusters(&nc, attn_kernel<false>, &cfg) == cudaSuccess && nc * CL >= NCTAS;
      cfg.gridDim = dim3(NCTAS + NHELP);
      help = fused && cudaOccupancyMaxActiveClusters(&nc, attn_kernel<true>, &cfg) == cudaSuccess && nc * CL >= NCTAS + NHELP;
    }
    void* fn = nullptr;
    cudaDriverEntryPointQueryResult qres;
    cudaGetDriverEntryPoint("cuTensorMapEncodeTiled", &fn, cudaEnableDefault, &qres);
    encode = (EncodeTiledFn)fn;
  }
  CUtensorMap tmq, tmq0;
  for (int m = 0; m < 2; m++) {
    const cuuint64_t dims[2] = {(cuuint64_t)DH, (cuuint64_t)HQ * SQ};
    const cuuint64_t strides[1] = {(cuuint64_t)DH * 2};
    const cuuint32_t box[2] = {64, m ? 64u : (cuuint32_t)QROWS};
    const cuuint32_t estr[2] = {1, 1};
    encode(m ? &tmq0 : &tmq, CU_TENSOR_MAP_DATA_TYPE_BFLOAT16, 2, d_in[0], dims, strides, box, estr, CU_TENSOR_MAP_INTERLEAVE_NONE, CU_TENSOR_MAP_SWIZZLE_128B,
           CU_TENSOR_MAP_L2_PROMOTION_L2_256B, CU_TENSOR_MAP_FLOAT_OOB_FILL_NONE);
  }
  const DqCtx dq = {qk, qv, ks, kz, vs, vz, scr};
  if (!fused) dequant_kernel<<<(2 * HKV * SKV) / (8 * 4), 256>>>(qk, qv, ks, kz, vs, vz, scr);
  if (help) attn_kernel<true><<<NCTAS + NHELP, 384, SMEM_BYTES>>>(dq, (const __nv_bfloat16*)d_in[0], out, 0u, fused, tmq, tmq0);
  else attn_kernel<false><<<NCTAS, 384, SMEM_BYTES>>>(dq, (const __nv_bfloat16*)d_in[0], out, 0u, fused, tmq, tmq0);
}
```
